```python
import torch

def _softmax(x, axis=-1):
    return torch.softmax(x, dim=axis)

def _gelu(x):
    return torch.nn.functional.gelu(x, approximate='tanh')

def _silu(x):
    return torch.nn.functional.silu(x)

def _sigmoid(x):
    return torch.sigmoid(x)

def _layernorm(x, axis=-1, eps=1e-05):
    m = x.mean(dim=axis, keepdim=True)
    v = x.var(dim=axis, keepdim=True, unbiased=False)
    return (x - m) / torch.sqrt(v + eps)

def _scatter_add(tgt, idx, src, axis=0):
    return tgt.clone().index_add_(axis, idx, src)

def _segment_sum(src, seg, n):
    out = torch.zeros((n,) + src.shape[1:], dtype=src.dtype)
    return out.index_add_(0, seg, src)

def _pad(x, pw):
    flat = tuple((v for pair in reversed(pw) for v in pair))
    return torch.nn.functional.pad(x, flat)
kernel_name = 'sequential_preLN__mha_block__mixer_gmlp__prompt'

def setup_inputs():

    _w = lambda a: (lambda t: t.to(torch.bfloat16) if t.is_floating_point() else t)(torch.as_tensor(a))

    def _A_setup():
        B, S, D, H = (1, 2048, 512, 32)
        return {'x': _w((lambda *s: torch.randn(*s, dtype=torch.bfloat16) * 0.05)(B, S, D)), 'wqkv': _w((lambda *s: torch.randn(*s, dtype=torch.bfloat16) * 0.05)(D, 3 * D)), 'wo': _w((lambda *s: torch.randn(*s, dtype=torch.bfloat16) * 0.05)(D, D))}
    _A_in = _A_setup()

    def _B_setup():
        B, S, D, F = (1, 2048, 512, 1792)
        Fh = F // 2
        return {'x': _w((lambda *s: torch.randn(*s, dtype=torch.bfloat16) * 0.05)(B, S, D)), 'w_in': _w((lambda *s: torch.randn(*s, dtype=torch.bfloat16) * 0.4)(D, 2 * Fh)), 'w_sp': _w(0.01 * (lambda *s: torch.randn(*s, dtype=torch.bfloat16) * 0.4)(S, S)), 'b_sp': _w(1.0 + 0.01 * (lambda *s: torch.randn(*s, dtype=torch.bfloat16) * 0.05)(S)), 'w_out': _w((lambda *s: torch.randn(*s, dtype=torch.bfloat16) * 0.05)(Fh, D))}
    _B_in = _B_setup()
    return {'A_x': _A_in['x'], 'A_wqkv': _A_in['wqkv'], 'A_wo': _A_in['wo'], 'B_x': _B_in['x'], 'B_w_in': _B_in['w_in'], 'B_w_sp': _B_in['w_sp'], 'B_b_sp': _B_in['b_sp'], 'B_w_out': _B_in['w_out']}

def reference(A_x, A_wqkv, A_wo, B_x, B_w_in, B_w_sp, B_b_sp, B_w_out):

    def _A_ref(x, wqkv, wo):
        B, S, D = x.shape
        H = 32
        Dh = D // H
        qkv = (lambda x, *d: x.permute(*d))((x @ wqkv).reshape(B, S, 3, H, Dh), 2, 0, 3, 1, 4)
        q, k, v = (qkv[0], qkv[1], qkv[2])
        scores = torch.einsum('bhqd,bhkd->bhqk', q, k) * Dh ** (-0.5)
        p = _softmax(scores, axis=-1)
        o = torch.einsum('bhqk,bhkd->bhqd', p, v)
        return (lambda x, *d: x.permute(*d))(o, 0, 2, 1, 3).reshape(B, S, D) @ wo

    def _B_ref(x, w_in, w_sp, b_sp, w_out):
        B, S, D = x.shape
        F = w_in.shape[-1]
        Fh = F // 2
        z = _gelu(torch.einsum('bsd,df->bsf', x, w_in))
        z1 = z[..., :Fh].clone()
        z2 = _layernorm(z[..., Fh:], axis=-1)
        g = torch.einsum('ts,bsf->btf', w_sp, z2) + b_sp[None, :, None]
        return torch.einsum('bsf,fd->bsd', z1 * g, w_out)
    x = A_x
    h = x + _A_ref(_layernorm(x, axis=-1), A_wqkv, A_wo)
    h2 = h + _B_ref(_layernorm(h, axis=-1), B_w_in, B_w_sp, B_b_sp, B_w_out)
    return h2
```

```cpp
#include <cuda_runtime.h>
#include <cuda.h>
#include <cuda_bf16.h>
#include <stdint.h>
#include <string.h>

typedef __nv_bfloat16 bf16;
#define DESC_MODE 0

__device__ __align__(1024) bf16 g_qkv[32 * 16 * 6 * 1024];
__device__ __align__(16) uint32_t g_kmax[8 * 128];
__device__ __align__(1024) bf16 g_o[2048 * 512];
__device__ __align__(1024) bf16 g_h[2048 * 512];
__device__ __align__(1024) bf16 g_z2[2048 * 896];
__device__ __align__(1024) bf16 g_u[2048 * 896];
__device__ __align__(1024) bf16 g_wt[7 * 14 * 80 * 64];
__device__ __align__(16) float g_cs_in[1792];
__device__ __align__(16) float2 g_hpart[2048 * 8];
constexpr int XP_X = 0, XP_W = 2048 * 8, XP_Z = XP_W + 8 * 16 * 96, XP_F = XP_Z + 2048 * 8, XP_U = XP_F + 128, XP_N = XP_U + 256;
__device__ __align__(128) uint2 g_xp[XP_N];

#define TS(k, i) do {} while (0)
__device__ __forceinline__ uint32_t smem_u32(const void* p) { return (uint32_t)__cvta_generic_to_shared(p); }
__device__ __forceinline__ void mbar_init(uint32_t bar, int cnt) { asm volatile("mbarrier.init.shared::cta.b64 [%0], %1;" ::"r"(bar), "r"(cnt) : "memory"); }
__device__ __forceinline__ void mbar_expect_tx(uint32_t bar, uint32_t bytes) { asm volatile("mbarrier.arrive.expect_tx.shared::cta.b64 _, [%0], %1;" ::"r"(bar), "r"(bytes) : "memory"); }
__device__ __forceinline__ void mbar_arrive(uint32_t bar) { asm volatile("mbarrier.arrive.shared::cta.b64 _, [%0];" ::"r"(bar) : "memory"); }
__device__ __forceinline__ void mbar_arrive_cluster(uint32_t bar, uint32_t cta) {
    asm volatile("{\n.reg .b32 ra;\nmapa.shared::cluster.u32 ra, %0, %1;\nmbarrier.arrive.shared::cluster.b64 _, [ra];\n}" ::"r"(bar), "r"(cta) : "memory");
}
__device__ __forceinline__ uint32_t clock32() { uint32_t c; asm volatile("mov.u32 %0, %%clock;" : "=r"(c)); return c; }
__device__ __forceinline__ uint32_t mbar_try(uint32_t bar, uint32_t parity) {
    uint32_t ok;
    asm volatile("{\n.reg .pred p;\nmbarrier.try_wait.parity.shared::cta.b64 p, [%1], %2;\nselp.u32 %0, 1, 0, p;\n}" : "=r"(ok) : "r"(bar), "r"(parity) : "memory");
    return ok;
}
__device__ __forceinline__ void mbar_wait(uint32_t bar, uint32_t parity) {
#pragma unroll 1
    for (uint32_t n = 0; !mbar_try(bar, parity); n++)
        if (n > 0x100000u) __trap();
}
__device__ __forceinline__ void fence_mbar_init() { asm volatile("fence.mbarrier_init.release.cluster;" ::: "memory"); }
__device__ __forceinline__ void fence_proxy_async() { asm volatile("fence.proxy.async.shared::cta;" ::: "memory"); }
__device__ __forceinline__ void cluster_sync_relaxed() {
    asm volatile("barrier.cluster.arrive.relaxed.aligned;\nbarrier.cluster.wait.aligned;" ::: "memory");
}
__device__ __forceinline__ uint4 ld_vol128(const void* p) { uint4 v; asm volatile("ld.volatile.global.v4.u32 {%0,%1,%2,%3}, [%4];" : "=r"(v.x), "=r"(v.y), "=r"(v.z), "=r"(v.w) : "l"(p) : "memory"); return v; }
__device__ __forceinline__ uint2 ld_vol64(const void* p) { uint2 v; asm volatile("ld.volatile.global.v2.u32 {%0,%1}, [%2];" : "=r"(v.x), "=r"(v.y) : "l"(p) : "memory"); return v; }
__device__ __forceinline__ void st_vol64(void* p, uint32_t a, uint32_t b) { asm volatile("st.volatile.global.v2.u32 [%0], {%1,%2};" ::"l"(p), "r"(a), "r"(b) : "memory"); }
__device__ __forceinline__ uint32_t cluster_rank() { uint32_t r; asm("mov.u32 %0, %%cluster_ctarank;" : "=r"(r)); return r; }
__device__ __forceinline__ void pdl_wait() { asm volatile("griddepcontrol.wait;" ::: "memory"); }
__device__ __forceinline__ void pdl_launch() { asm volatile("griddepcontrol.launch_dependents;" ::: "memory"); }
__device__ __forceinline__ void bar_sync(int id, int n) { asm volatile("bar.sync %0, %1;" ::"r"(id), "r"(n) : "memory"); }
__device__ __forceinline__ void bar_arrive(int id, int n) { asm volatile("bar.arrive %0, %1;" ::"r"(id), "r"(n) : "memory"); }
__device__ __forceinline__ void prefetch_tmap(const CUtensorMap* tm) { asm volatile("prefetch.tensormap [%0];" ::"l"(tm) : "memory"); }

__device__ __forceinline__ void tma_2d(uint32_t dst, const CUtensorMap* tm, uint32_t bar, int c0, int c1) {
    asm volatile("cp.async.bulk.tensor.2d.shared::cluster.global.mbarrier::complete_tx::bytes [%0], [%1, {%3, %4}], [%2];"
                 ::"r"(dst), "l"(tm), "r"(bar), "r"(c0), "r"(c1) : "memory");
}
__device__ __forceinline__ void tma_2d_mc(uint32_t dst, const CUtensorMap* tm, uint32_t bar, int c0, int c1, uint16_t mask) {
    asm volatile("cp.async.bulk.tensor.2d.shared::cluster.global.mbarrier::complete_tx::bytes.multicast::cluster [%0], [%1, {%3, %4}], [%2], %5;"
                 ::"r"(dst), "l"(tm), "r"(bar), "r"(c0), "r"(c1), "h"(mask) : "memory");
}
__device__ __forceinline__ void tma_3d_mc(uint32_t dst, const CUtensorMap* tm, uint32_t bar, int c0, int c1, int c2, uint16_t mask) {
    asm volatile("cp.async.bulk.tensor.3d.shared::cluster.global.mbarrier::complete_tx::bytes.multicast::cluster [%0], [%1, {%3, %4, %5}], [%2], %6;"
                 ::"r"(dst), "l"(tm), "r"(bar), "r"(c0), "r"(c1), "r"(c2), "h"(mask) : "memory");
}
__device__ __forceinline__ void tma_store_2d(const CUtensorMap* tm, uint32_t src, int c0, int c1) {
    asm volatile("cp.async.bulk.tensor.2d.global.shared::cta.bulk_group [%0, {%2, %3}], [%1];" ::"l"(tm), "r"(src), "r"(c0), "r"(c1) : "memory");
}
__device__ __forceinline__ void bulk_commit() { asm volatile("cp.async.bulk.commit_group;" ::: "memory"); }
__device__ __forceinline__ void bulk_wait_read() { asm volatile("cp.async.bulk.wait_group.read 0;" ::: "memory"); }
__device__ __forceinline__ void bulk_wait0() { asm volatile("cp.async.bulk.wait_group 0;" ::: "memory"); }
__device__ __forceinline__ void bulk_load(uint32_t dst, const void* src, uint32_t bytes, uint32_t bar) {
    asm volatile("cp.async.bulk.shared::cluster.global.mbarrier::complete_tx::bytes [%0], [%1], %2, [%3];" ::"r"(dst), "l"(src), "r"(bytes), "r"(bar) : "memory");
}
__device__ __forceinline__ void prefetch_l2(const void* src, uint32_t bytes) {
    asm volatile("cp.async.bulk.prefetch.L2.global [%0], %1;" ::"l"(src), "r"(bytes) : "memory");
}
__device__ __forceinline__ uint64_t mkdesc(uint32_t addr, uint32_t lbo, uint32_t sbo, uint32_t mode) {
    return (uint64_t)((addr & 0x3FFFF) >> 4) | ((uint64_t)(lbo >> 4) << 16) | ((uint64_t)(sbo >> 4) << 32) | ((uint64_t)mode << 62);
}
__device__ __forceinline__ uint32_t desc_lo(uint32_t addr, uint32_t lbo) { return ((addr & 0x3FFFF) >> 4) | ((lbo >> 4) << 16); }
__device__ __forceinline__ uint64_t desc64(uint32_t lo, uint32_t hi) { uint64_t d; asm("mov.b64 %0, {%1, %2};" : "=l"(d) : "r"(lo), "r"(hi)); return d; }
__device__ __forceinline__ void desc_add(uint64_t& d, uint32_t inc) {
    asm("{\n.reg .b32 l, h;\nmov.b64 {l, h}, %0;\nadd.u32 l, l, %1;\nmov.b64 %0, {l, h};\n}" : "+l"(d) : "r"(inc));
}
__device__ __forceinline__ void wg_fence() { asm volatile("wgmma.fence.sync.aligned;" ::: "memory"); }
__device__ __forceinline__ void wg_commit() { asm volatile("wgmma.commit_group.sync.aligned;" ::: "memory"); }
template <int N> __device__ __forceinline__ void wg_wait() { asm volatile("wgmma.wait_group.sync.aligned %0;" ::"n"(N) : "memory"); }
template <int N> __device__ __forceinline__ void fence_regs(float (&d)[N]) {
#pragma unroll
    for (int i = 0; i < N; i++) asm volatile("" : "+f"(d[i])::"memory");
}
__device__ __forceinline__ uint32_t pack_bf16(float lo, float hi) {
    uint32_t r; asm("cvt.rn.bf16x2.f32 %0, %1, %2;" : "=r"(r) : "f"(hi), "f"(lo)); return r;
}
__device__ __forceinline__ float bf_lo(uint32_t v) { return __uint_as_float(v << 16); }
__device__ __forceinline__ float bf_hi(uint32_t v) { return __uint_as_float(v & 0xFFFF0000u); }
__device__ __forceinline__ uint4 lds128(uint32_t a) { uint4 v; asm volatile("ld.shared.v4.u32 {%0,%1,%2,%3}, [%4];" : "=r"(v.x), "=r"(v.y), "=r"(v.z), "=r"(v.w) : "r"(a)); return v; }
__device__ __forceinline__ float4 lds128f(uint32_t a) { float4 v; asm volatile("ld.shared.v4.f32 {%0,%1,%2,%3}, [%4];" : "=f"(v.x), "=f"(v.y), "=f"(v.z), "=f"(v.w) : "r"(a)); return v; }
__device__ __forceinline__ float2 lds64f(uint32_t a) { float2 v; asm volatile("ld.shared.v2.f32 {%0,%1}, [%2];" : "=f"(v.x), "=f"(v.y) : "r"(a)); return v; }
__device__ __forceinline__ void stsm4(uint32_t a, uint32_t r0, uint32_t r1, uint32_t r2, uint32_t r3) {
    asm volatile("stmatrix.sync.aligned.m8n8.x4.shared.b16 [%0], {%1,%2,%3,%4};" ::"r"(a), "r"(r0), "r"(r1), "r"(r2), "r"(r3) : "memory");
}
__device__ __forceinline__ void stsm4_t(uint32_t a, uint32_t r0, uint32_t r1, uint32_t r2, uint32_t r3) {
    asm volatile("stmatrix.sync.aligned.m8n8.x4.trans.shared.b16 [%0], {%1,%2,%3,%4};" ::"r"(a), "r"(r0), "r"(r1), "r"(r2), "r"(r3) : "memory");
}
__device__ __forceinline__ void ldsm4(uint32_t a, uint32_t& r0, uint32_t& r1, uint32_t& r2, uint32_t& r3) {
    asm volatile("ldmatrix.sync.aligned.m8n8.x4.shared.b16 {%0,%1,%2,%3}, [%4];" : "=r"(r0), "=r"(r1), "=r"(r2), "=r"(r3) : "r"(a) : "memory");
}
__device__ __forceinline__ uint32_t lds32(uint32_t a) { uint32_t v; asm volatile("ld.shared.u32 %0, [%1];" : "=r"(v) : "r"(a)); return v; }
__device__ __forceinline__ void sts64f(uint32_t a, float x, float y) { asm volatile("st.shared.v2.f32 [%0], {%1,%2};" ::"r"(a), "f"(x), "f"(y) : "memory"); }
__device__ __forceinline__ void bulk_store(void* dst, uint32_t src, uint32_t bytes) {
    asm volatile("cp.async.bulk.global.shared::cta.bulk_group [%0], [%1], %2;" ::"l"(dst), "r"(src), "r"(bytes) : "memory");
}
constexpr uint32_t SW_HI = 0x40000040u;
__device__ __forceinline__ float quad_sum(float v) { v += __shfl_xor_sync(~0u, v, 1); return v + __shfl_xor_sync(~0u, v, 2); }
__device__ __forceinline__ void ldsm4_t(uint32_t a, uint32_t& r0, uint32_t& r1, uint32_t& r2, uint32_t& r3) {
    asm volatile("ldmatrix.sync.aligned.m8n8.x4.trans.shared.b16 {%0,%1,%2,%3}, [%4];" : "=r"(r0), "=r"(r1), "=r"(r2), "=r"(r3) : "r"(a) : "memory");
}
__device__ __forceinline__ float ex2f(float x) { float r; asm("ex2.approx.ftz.f32 %0, %1;" : "=f"(r) : "f"(x)); return r; }
__device__ __forceinline__ float tanhf_(float x) { float r; asm("tanh.approx.f32 %0, %1;" : "=f"(r) : "f"(x)); return r; }
__device__ __forceinline__ float gelu_tanh(float z) {
    float t = z * z;
    float in = z * fmaf(t, 0.7978845608028654f * 0.044715f, 0.7978845608028654f);
    float hz = 0.5f * z;
    return fmaf(hz, tanhf_(in), hz);
}
__device__ __forceinline__ void red_add(float* p, float v) { asm volatile("red.global.add.f32 [%0], %1;" ::"l"(p), "f"(v) : "memory"); }
__device__ __forceinline__ float2 ln_params(float s, float q, float inv_n) {
    float m = s * inv_n;
    float var = fmaxf(fmaf(-m, m, q * inv_n), 0.f);
    float r = rsqrtf(var + 1e-5f);
    return make_float2(r, -m * r);
}

template<int TA, int TB> __device__ __forceinline__ void wgmma_ss0_n64(float (&d)[32], uint64_t da, uint64_t db) {
    asm volatile(
        "wgmma.mma_async.sync.aligned.m64n64k16.f32.bf16.bf16 {%0, %1, %2, %3, %4, %5, %6, %7, %8, %9, %10, %11, %12, %13, %14, %15, %16, %17, %18, %19, %20, %21, %22, %23, %24, %25, %26, %27, %28, %29, %30, %31}, %32, %33, 0, 1, 1, %34, %35;\n"
        : "=f"(d[0]), "=f"(d[1]), "=f"(d[2]), "=f"(d[3]), "=f"(d[4]), "=f"(d[5]), "=f"(d[6]), "=f"(d[7]), "=f"(d[8]), "=f"(d[9]), "=f"(d[10]), "=f"(d[11]), "=f"(d[12]), "=f"(d[13]), "=f"(d[14]), "=f"(d[15]), "=f"(d[16]), "=f"(d[17]), "=f"(d[18]), "=f"(d[19]), "=f"(d[20]), "=f"(d[21]), "=f"(d[22]), "=f"(d[23]), "=f"(d[24]), "=f"(d[25]), "=f"(d[26]), "=f"(d[27]), "=f"(d[28]), "=f"(d[29]), "=f"(d[30]), "=f"(d[31])
        : "l"(da), "l"(db), "n"(TA), "n"(TB));
}

template<int TA, int TB> __device__ __forceinline__ void wgmma_ss1_n64(float (&d)[32], uint64_t da, uint64_t db) {
    asm volatile(
        "wgmma.mma_async.sync.aligned.m64n64k16.f32.bf16.bf16 {%0, %1, %2, %3, %4, %5, %6, %7, %8, %9, %10, %11, %12, %13, %14, %15, %16, %17, %18, %19, %20, %21, %22, %23, %24, %25, %26, %27, %28, %29, %30, %31}, %32, %33, 1, 1, 1, %34, %35;\n"
        : "+f"(d[0]), "+f"(d[1]), "+f"(d[2]), "+f"(d[3]), "+f"(d[4]), "+f"(d[5]), "+f"(d[6]), "+f"(d[7]), "+f"(d[8]), "+f"(d[9]), "+f"(d[10]), "+f"(d[11]), "+f"(d[12]), "+f"(d[13]), "+f"(d[14]), "+f"(d[15]), "+f"(d[16]), "+f"(d[17]), "+f"(d[18]), "+f"(d[19]), "+f"(d[20]), "+f"(d[21]), "+f"(d[22]), "+f"(d[23]), "+f"(d[24]), "+f"(d[25]), "+f"(d[26]), "+f"(d[27]), "+f"(d[28]), "+f"(d[29]), "+f"(d[30]), "+f"(d[31])
        : "l"(da), "l"(db), "n"(TA), "n"(TB));
}

template<int TA, int TB> __device__ __forceinline__ void wgmma_ss0_n128(float (&d)[64], uint64_t da, uint64_t db) {
    asm volatile(
        "wgmma.mma_async.sync.aligned.m64n128k16.f32.bf16.bf16 {%0, %1, %2, %3, %4, %5, %6, %7, %8, %9, %10, %11, %12, %13, %14, %15, %16, %17, %18, %19, %20, %21, %22, %23, %24, %25, %26, %27, %28, %29, %30, %31, %32, %33, %34, %35, %36, %37, %38, %39, %40, %41, %42, %43, %44, %45, %46, %47, %48, %49, %50, %51, %52, %53, %54, %55, %56, %57, %58, %59, %60, %61, %62, %63}, %64, %65, 0, 1, 1, %66, %67;\n"
        : "=f"(d[0]), "=f"(d[1]), "=f"(d[2]), "=f"(d[3]), "=f"(d[4]), "=f"(d[5]), "=f"(d[6]), "=f"(d[7]), "=f"(d[8]), "=f"(d[9]), "=f"(d[10]), "=f"(d[11]), "=f"(d[12]), "=f"(d[13]), "=f"(d[14]), "=f"(d[15]), "=f"(d[16]), "=f"(d[17]), "=f"(d[18]), "=f"(d[19]), "=f"(d[20]), "=f"(d[21]), "=f"(d[22]), "=f"(d[23]), "=f"(d[24]), "=f"(d[25]), "=f"(d[26]), "=f"(d[27]), "=f"(d[28]), "=f"(d[29]), "=f"(d[30]), "=f"(d[31]), "=f"(d[32]), "=f"(d[33]), "=f"(d[34]), "=f"(d[35]), "=f"(d[36]), "=f"(d[37]), "=f"(d[38]), "=f"(d[39]), "=f"(d[40]), "=f"(d[41]), "=f"(d[42]), "=f"(d[43]), "=f"(d[44]), "=f"(d[45]), "=f"(d[46]), "=f"(d[47]), "=f"(d[48]), "=f"(d[49]), "=f"(d[50]), "=f"(d[51]), "=f"(d[52]), "=f"(d[53]), "=f"(d[54]), "=f"(d[55]), "=f"(d[56]), "=f"(d[57]), "=f"(d[58]), "=f"(d[59]), "=f"(d[60]), "=f"(d[61]), "=f"(d[62]), "=f"(d[63])
        : "l"(da), "l"(db), "n"(TA), "n"(TB));
}

template<int TA, int TB> __device__ __forceinline__ void wgmma_ss1_n128(float (&d)[64], uint64_t da, uint64_t db) {
    asm volatile(
        "wgmma.mma_async.sync.aligned.m64n128k16.f32.bf16.bf16 {%0, %1, %2, %3, %4, %5, %6, %7, %8, %9, %10, %11, %12, %13, %14, %15, %16, %17, %18, %19, %20, %21, %22, %23, %24, %25, %26, %27, %28, %29, %30, %31, %32, %33, %34, %35, %36, %37, %38, %39, %40, %41, %42, %43, %44, %45, %46, %47, %48, %49, %50, %51, %52, %53, %54, %55, %56, %57, %58, %59, %60, %61, %62, %63}, %64, %65, 1, 1, 1, %66, %67;\n"
        : "+f"(d[0]), "+f"(d[1]), "+f"(d[2]), "+f"(d[3]), "+f"(d[4]), "+f"(d[5]), "+f"(d[6]), "+f"(d[7]), "+f"(d[8]), "+f"(d[9]), "+f"(d[10]), "+f"(d[11]), "+f"(d[12]), "+f"(d[13]), "+f"(d[14]), "+f"(d[15]), "+f"(d[16]), "+f"(d[17]), "+f"(d[18]), "+f"(d[19]), "+f"(d[20]), "+f"(d[21]), "+f"(d[22]), "+f"(d[23]), "+f"(d[24]), "+f"(d[25]), "+f"(d[26]), "+f"(d[27]), "+f"(d[28]), "+f"(d[29]), "+f"(d[30]), "+f"(d[31]), "+f"(d[32]), "+f"(d[33]), "+f"(d[34]), "+f"(d[35]), "+f"(d[36]), "+f"(d[37]), "+f"(d[38]), "+f"(d[39]), "+f"(d[40]), "+f"(d[41]), "+f"(d[42]), "+f"(d[43]), "+f"(d[44]), "+f"(d[45]), "+f"(d[46]), "+f"(d[47]), "+f"(d[48]), "+f"(d[49]), "+f"(d[50]), "+f"(d[51]), "+f"(d[52]), "+f"(d[53]), "+f"(d[54]), "+f"(d[55]), "+f"(d[56]), "+f"(d[57]), "+f"(d[58]), "+f"(d[59]), "+f"(d[60]), "+f"(d[61]), "+f"(d[62]), "+f"(d[63])
        : "l"(da), "l"(db), "n"(TA), "n"(TB));
}

template<int TA, int TB> __device__ __forceinline__ void wgmma_ss0_n192(float (&d)[96], uint64_t da, uint64_t db) {
    asm volatile(
        "wgmma.mma_async.sync.aligned.m64n192k16.f32.bf16.bf16 {%0, %1, %2, %3, %4, %5, %6, %7, %8, %9, %10, %11, %12, %13, %14, %15, %16, %17, %18, %19, %20, %21, %22, %23, %24, %25, %26, %27, %28, %29, %30, %31, %32, %33, %34, %35, %36, %37, %38, %39, %40, %41, %42, %43, %44, %45, %46, %47, %48, %49, %50, %51, %52, %53, %54, %55, %56, %57, %58, %59, %60, %61, %62, %63, %64, %65, %66, %67, %68, %69, %70, %71, %72, %73, %74, %75, %76, %77, %78, %79, %80, %81, %82, %83, %84, %85, %86, %87, %88, %89, %90, %91, %92, %93, %94, %95}, %96, %97, 0, 1, 1, %98, %99;\n"
        : "=f"(d[0]), "=f"(d[1]), "=f"(d[2]), "=f"(d[3]), "=f"(d[4]), "=f"(d[5]), "=f"(d[6]), "=f"(d[7]), "=f"(d[8]), "=f"(d[9]), "=f"(d[10]), "=f"(d[11]), "=f"(d[12]), "=f"(d[13]), "=f"(d[14]), "=f"(d[15]), "=f"(d[16]), "=f"(d[17]), "=f"(d[18]), "=f"(d[19]), "=f"(d[20]), "=f"(d[21]), "=f"(d[22]), "=f"(d[23]), "=f"(d[24]), "=f"(d[25]), "=f"(d[26]), "=f"(d[27]), "=f"(d[28]), "=f"(d[29]), "=f"(d[30]), "=f"(d[31]), "=f"(d[32]), "=f"(d[33]), "=f"(d[34]), "=f"(d[35]), "=f"(d[36]), "=f"(d[37]), "=f"(d[38]), "=f"(d[39]), "=f"(d[40]), "=f"(d[41]), "=f"(d[42]), "=f"(d[43]), "=f"(d[44]), "=f"(d[45]), "=f"(d[46]), "=f"(d[47]), "=f"(d[48]), "=f"(d[49]), "=f"(d[50]), "=f"(d[51]), "=f"(d[52]), "=f"(d[53]), "=f"(d[54]), "=f"(d[55]), "=f"(d[56]), "=f"(d[57]), "=f"(d[58]), "=f"(d[59]), "=f"(d[60]), "=f"(d[61]), "=f"(d[62]), "=f"(d[63]), "=f"(d[64]), "=f"(d[65]), "=f"(d[66]), "=f"(d[67]), "=f"(d[68]), "=f"(d[69]), "=f"(d[70]), "=f"(d[71]), "=f"(d[72]), "=f"(d[73]), "=f"(d[74]), "=f"(d[75]), "=f"(d[76]), "=f"(d[77]), "=f"(d[78]), "=f"(d[79]), "=f"(d[80]), "=f"(d[81]), "=f"(d[82]), "=f"(d[83]), "=f"(d[84]), "=f"(d[85]), "=f"(d[86]), "=f"(d[87]), "=f"(d[88]), "=f"(d[89]), "=f"(d[90]), "=f"(d[91]), "=f"(d[92]), "=f"(d[93]), "=f"(d[94]), "=f"(d[95])
        : "l"(da), "l"(db), "n"(TA), "n"(TB));
}

template<int TA, int TB> __device__ __forceinline__ void wgmma_ss1_n192(float (&d)[96], uint64_t da, uint64_t db) {
    asm volatile(
        "wgmma.mma_async.sync.aligned.m64n192k16.f32.bf16.bf16 {%0, %1, %2, %3, %4, %5, %6, %7, %8, %9, %10, %11, %12, %13, %14, %15, %16, %17, %18, %19, %20, %21, %22, %23, %24, %25, %26, %27, %28, %29, %30, %31, %32, %33, %34, %35, %36, %37, %38, %39, %40, %41, %42, %43, %44, %45, %46, %47, %48, %49, %50, %51, %52, %53, %54, %55, %56, %57, %58, %59, %60, %61, %62, %63, %64, %65, %66, %67, %68, %69, %70, %71, %72, %73, %74, %75, %76, %77, %78, %79, %80, %81, %82, %83, %84, %85, %86, %87, %88, %89, %90, %91, %92, %93, %94, %95}, %96, %97, 1, 1, 1, %98, %99;\n"
        : "+f"(d[0]), "+f"(d[1]), "+f"(d[2]), "+f"(d[3]), "+f"(d[4]), "+f"(d[5]), "+f"(d[6]), "+f"(d[7]), "+f"(d[8]), "+f"(d[9]), "+f"(d[10]), "+f"(d[11]), "+f"(d[12]), "+f"(d[13]), "+f"(d[14]), "+f"(d[15]), "+f"(d[16]), "+f"(d[17]), "+f"(d[18]), "+f"(d[19]), "+f"(d[20]), "+f"(d[21]), "+f"(d[22]), "+f"(d[23]), "+f"(d[24]), "+f"(d[25]), "+f"(d[26]), "+f"(d[27]), "+f"(d[28]), "+f"(d[29]), "+f"(d[30]), "+f"(d[31]), "+f"(d[32]), "+f"(d[33]), "+f"(d[34]), "+f"(d[35]), "+f"(d[36]), "+f"(d[37]), "+f"(d[38]), "+f"(d[39]), "+f"(d[40]), "+f"(d[41]), "+f"(d[42]), "+f"(d[43]), "+f"(d[44]), "+f"(d[45]), "+f"(d[46]), "+f"(d[47]), "+f"(d[48]), "+f"(d[49]), "+f"(d[50]), "+f"(d[51]), "+f"(d[52]), "+f"(d[53]), "+f"(d[54]), "+f"(d[55]), "+f"(d[56]), "+f"(d[57]), "+f"(d[58]), "+f"(d[59]), "+f"(d[60]), "+f"(d[61]), "+f"(d[62]), "+f"(d[63]), "+f"(d[64]), "+f"(d[65]), "+f"(d[66]), "+f"(d[67]), "+f"(d[68]), "+f"(d[69]), "+f"(d[70]), "+f"(d[71]), "+f"(d[72]), "+f"(d[73]), "+f"(d[74]), "+f"(d[75]), "+f"(d[76]), "+f"(d[77]), "+f"(d[78]), "+f"(d[79]), "+f"(d[80]), "+f"(d[81]), "+f"(d[82]), "+f"(d[83]), "+f"(d[84]), "+f"(d[85]), "+f"(d[86]), "+f"(d[87]), "+f"(d[88]), "+f"(d[89]), "+f"(d[90]), "+f"(d[91]), "+f"(d[92]), "+f"(d[93]), "+f"(d[94]), "+f"(d[95])
        : "l"(da), "l"(db), "n"(TA), "n"(TB));
}

template<int TB> __device__ __forceinline__ void wgmma_rs1_n24(float (&d)[12], uint32_t a0, uint32_t a1, uint32_t a2, uint32_t a3, uint64_t db) {
    asm volatile(
        "wgmma.mma_async.sync.aligned.m64n24k16.f32.bf16.bf16 {%0, %1, %2, %3, %4, %5, %6, %7, %8, %9, %10, %11}, {%12, %13, %14, %15}, %16, 1, 1, 1, %17;\n"
        : "+f"(d[0]), "+f"(d[1]), "+f"(d[2]), "+f"(d[3]), "+f"(d[4]), "+f"(d[5]), "+f"(d[6]), "+f"(d[7]), "+f"(d[8]), "+f"(d[9]), "+f"(d[10]), "+f"(d[11])
        : "r"(a0), "r"(a1), "r"(a2), "r"(a3), "l"(db), "n"(TB));
}

template<int TB> __device__ __forceinline__ void wgmma_rs_n24(float (&d)[12], uint32_t a0, uint32_t a1, uint32_t a2, uint32_t a3, uint64_t db, int sd) {
    asm volatile("{\n.reg .pred p;\nsetp.ne.b32 p, %17, 0;\n"
        "wgmma.mma_async.sync.aligned.m64n24k16.f32.bf16.bf16 {%0, %1, %2, %3, %4, %5, %6, %7, %8, %9, %10, %11}, {%12, %13, %14, %15}, %16, p, 1, 1, %18;\n}\n"
        : "+f"(d[0]), "+f"(d[1]), "+f"(d[2]), "+f"(d[3]), "+f"(d[4]), "+f"(d[5]), "+f"(d[6]), "+f"(d[7]), "+f"(d[8]), "+f"(d[9]), "+f"(d[10]), "+f"(d[11])
        : "r"(a0), "r"(a1), "r"(a2), "r"(a3), "l"(db), "r"(sd), "n"(TB));
}

template<int TA, int TB> __device__ __forceinline__ void wgmma_ss_n128(float (&d)[64], uint64_t da, uint64_t db, int sd) {
    asm volatile("{\n.reg .pred p;\nsetp.ne.b32 p, %66, 0;\n"
        "wgmma.mma_async.sync.aligned.m64n128k16.f32.bf16.bf16 {%0, %1, %2, %3, %4, %5, %6, %7, %8, %9, %10, %11, %12, %13, %14, %15, %16, %17, %18, %19, %20, %21, %22, %23, %24, %25, %26, %27, %28, %29, %30, %31, %32, %33, %34, %35, %36, %37, %38, %39, %40, %41, %42, %43, %44, %45, %46, %47, %48, %49, %50, %51, %52, %53, %54, %55, %56, %57, %58, %59, %60, %61, %62, %63}, %64, %65, p, 1, 1, %67, %68;\n}\n"
        : "+f"(d[0]), "+f"(d[1]), "+f"(d[2]), "+f"(d[3]), "+f"(d[4]), "+f"(d[5]), "+f"(d[6]), "+f"(d[7]), "+f"(d[8]), "+f"(d[9]), "+f"(d[10]), "+f"(d[11]), "+f"(d[12]), "+f"(d[13]), "+f"(d[14]), "+f"(d[15]), "+f"(d[16]), "+f"(d[17]), "+f"(d[18]), "+f"(d[19]), "+f"(d[20]), "+f"(d[21]), "+f"(d[22]), "+f"(d[23]), "+f"(d[24]), "+f"(d[25]), "+f"(d[26]), "+f"(d[27]), "+f"(d[28]), "+f"(d[29]), "+f"(d[30]), "+f"(d[31]), "+f"(d[32]), "+f"(d[33]), "+f"(d[34]), "+f"(d[35]), "+f"(d[36]), "+f"(d[37]), "+f"(d[38]), "+f"(d[39]), "+f"(d[40]), "+f"(d[41]), "+f"(d[42]), "+f"(d[43]), "+f"(d[44]), "+f"(d[45]), "+f"(d[46]), "+f"(d[47]), "+f"(d[48]), "+f"(d[49]), "+f"(d[50]), "+f"(d[51]), "+f"(d[52]), "+f"(d[53]), "+f"(d[54]), "+f"(d[55]), "+f"(d[56]), "+f"(d[57]), "+f"(d[58]), "+f"(d[59]), "+f"(d[60]), "+f"(d[61]), "+f"(d[62]), "+f"(d[63])
        : "l"(da), "l"(db), "r"(sd), "n"(TA), "n"(TB));
}

template<int TA, int TB> __device__ __forceinline__ void wgmma_ss1_n80(float (&d)[40], uint64_t da, uint64_t db) {
    asm volatile(
        "wgmma.mma_async.sync.aligned.m64n80k16.f32.bf16.bf16 {%0, %1, %2, %3, %4, %5, %6, %7, %8, %9, %10, %11, %12, %13, %14, %15, %16, %17, %18, %19, %20, %21, %22, %23, %24, %25, %26, %27, %28, %29, %30, %31, %32, %33, %34, %35, %36, %37, %38, %39}, %40, %41, 1, 1, 1, %42, %43;\n"
        : "+f"(d[0]), "+f"(d[1]), "+f"(d[2]), "+f"(d[3]), "+f"(d[4]), "+f"(d[5]), "+f"(d[6]), "+f"(d[7]), "+f"(d[8]), "+f"(d[9]), "+f"(d[10]), "+f"(d[11]), "+f"(d[12]), "+f"(d[13]), "+f"(d[14]), "+f"(d[15]), "+f"(d[16]), "+f"(d[17]), "+f"(d[18]), "+f"(d[19]), "+f"(d[20]), "+f"(d[21]), "+f"(d[22]), "+f"(d[23]), "+f"(d[24]), "+f"(d[25]), "+f"(d[26]), "+f"(d[27]), "+f"(d[28]), "+f"(d[29]), "+f"(d[30]), "+f"(d[31]), "+f"(d[32]), "+f"(d[33]), "+f"(d[34]), "+f"(d[35]), "+f"(d[36]), "+f"(d[37]), "+f"(d[38]), "+f"(d[39])
        : "l"(da), "l"(db), "n"(TA), "n"(TB));
}

#define X_PRE 1
#define Q_PACE 3
#define Q_PEND 8
#define PF_PRE 2
#define PF_GAP 0
#define SP_MAX 3
#define STG_MASK 7
#define STG_FINE 1
#define POLL_NS 0
#define SLEEP_ST 7
constexpr int G1_ST = 5, G1_STB = 16384 + 24576;
#define BULK_ST 0
constexpr int G1_SMEM = G1_ST * G1_STB + 1024 + 1536 + 256 + 20480 + 1024;
__global__ void __cluster_dims__(2, 1, 1) __launch_bounds__(416, 1)
k_qkv(const __grid_constant__ CUtensorMap tm_x, const __grid_constant__ CUtensorMap tm_w, const bf16* __restrict__ x, const bf16* __restrict__ wqkv) {
    extern __shared__ uint8_t smem_raw[];
    const uint32_t sb = (smem_u32(smem_raw) + 1023) & ~1023u;
    const uint32_t s_row = sb + G1_ST * G1_STB;
    const uint32_t s_cs = s_row + 1024;
    const uint32_t s_bar = s_cs + 1536;
    const uint32_t s_par = s_bar + 256;
    const int tid = threadIdx.x, warp = __shfl_sync(~0u, tid >> 5, 0), lane = tid & 31;
    const uint32_t rank = cluster_rank();
    const int pair = blockIdx.x >> 1, nb = pair & 7, mb = (pair >> 3) * 2 + rank, rot = (nb + (pair >> 3)) & 7;
    const int sp = min(rot, SP_MAX);
    const uint32_t tstart = clock32();
    const bf16* pf = lane < 16 ? x + (blockIdx.x * 16 + lane) * 512 + warp * 64 : wqkv + warp * 64 * 1536 + (blockIdx.x * 12 + lane - 16) * 64;
    if (warp < PF_PRE && lane < 28) asm volatile("prefetch.global.L2 [%0];" ::"l"(pf));
    if (tid == 384) {
        TS(0, 0);
        prefetch_tmap(&tm_x); prefetch_tmap(&tm_w);
#pragma unroll
        for (int i = 0; i <= G1_ST; i++) mbar_init(s_bar + i * 8, 1);
        for (int i = 0; i < 3; i++) mbar_init(s_bar + 64 + i * 8, i == sp ? 12 : 4);
        fence_mbar_init();
#pragma unroll
        for (int i = 0; i < G1_ST; i++) {
            mbar_expect_tx(s_bar + i * 8, G1_STB);
            if (i < X_PRE) tma_2d(sb + i * G1_STB, &tm_x, s_bar + i * 8, i * 64, mb * 128);
        }
        pdl_launch();
    }
    __syncwarp();
    cluster_sync_relaxed();
    if (warp == 12) {
        if (lane == 0) {
#pragma unroll
            for (int i = 0; i < 8; i++) {
                const int s = i % G1_ST, kb = i < SP_MAX ? i : i == sp ? rot : i - (i <= rot);
                const uint32_t st = sb + s * G1_STB, fb = s_bar + s * 8;
                if (i >= G1_ST) {
                    mbar_wait(s_bar + 64 + s * 8, 0);
                    mbar_expect_tx(fb, G1_STB);
                }
                if (Q_PACE && i >= Q_PACE && i < Q_PEND) mbar_wait(s_bar + (i - Q_PACE) % G1_ST * 8, (i - Q_PACE) / G1_ST);
                if (i >= X_PRE) tma_2d(st, &tm_x, fb, kb * 64, mb * 128);
                TS(0, 32 + i);
                tma_3d_mc(st + 16384 + rank * 12288, &tm_w, fb, 0, kb * 64 + rank * 32, nb * 3, (uint16_t)3);
            }
        }
    } else if (warp >= 8) {
        const int t = tid - 256;
        mbar_wait(s_bar + sp * 8, 0);
        const uint32_t st = sb + sp * G1_STB;
        {
            float rs = 0.f, rq = 0.f;
#pragma unroll
            for (int i = 0; i < 8; i++) {
                uint4 v = lds128(st + t * 128 + ((i ^ (t & 7)) << 4));
                uint32_t w[4] = {v.x, v.y, v.z, v.w};
#pragma unroll
                for (int j = 0; j < 4; j++) {
                    float a = bf_lo(w[j]), b = bf_hi(w[j]);
                    rs += a; rq = fmaf(a, a, rq); rs += b; rq = fmaf(b, b, rq);
                }
            }
            st_vol64(g_xp + XP_X + (mb * 128 + t) * 8 + rot, __float_as_uint(rs), __float_as_uint(rq) | 0x80000000u);
        }
        if (t < 96) {
            const uint32_t wb = st + 16384 + rank * 12288 + (t >> 5) * 4096 + (t & 3) * 4;
            const int c = (t >> 2) & 7;
            float c0 = 0.f, c1 = 0.f;
#pragma unroll
            for (int r = 0; r < 32; r++) {
                uint32_t v = lds32(wb + r * 128 + ((c ^ (r & 7)) << 4));
                c0 += bf_lo(v); c1 += bf_hi(v);
            }
            st_vol64(g_xp + XP_W + (nb * 16 + rot * 2 + rank) * 96 + t, __float_as_uint(c0) | 1u, __float_as_uint(c1));
        }
        __syncwarp();
        if (lane < 2 && sp < 3) mbar_arrive_cluster(s_bar + 64 + sp * 8, lane);
        if (t == 0) TS(0, 1);
        mbar_wait(s_bar + (SLEEP_ST % G1_ST) * 8, SLEEP_ST / G1_ST);
        {
            const uint2* p = g_xp + XP_X + (mb * 128 + t) * 8;
            const uint2* pw = g_xp + XP_W + nb * 16 * 96 + (t & 63) * 2 + (t >> 6) * 8 * 96;
            const bool wl = (t & 63) < 48;
            uint4 v[4], u[8];
            uint32_t okx = 0, okw = !wl;
            for (int n = 0;; n++) {
                if (!okx) {
#pragma unroll
                    for (int i = 0; i < 4; i++) v[i] = ld_vol128(p + 2 * i);
                }
                if (!okw) {
#pragma unroll
                    for (int i = 0; i < 8; i++) u[i] = ld_vol128(pw + i * 96);
                }
                okx = 0x80000000u;
#pragma unroll
                for (int i = 0; i < 4; i++) okx &= v[i].y & v[i].w;
                if (wl) {
                    okw = 1u;
#pragma unroll
                    for (int i = 0; i < 8; i++) okw &= u[i].x & u[i].z;
                }
                if (okx && okw) break;
                if (n > 0x100000) __trap();
            }
            float rs = 0.f, rq = 0.f;
#pragma unroll
            for (int i = 0; i < 4; i++) {
                rs += __uint_as_float(v[i].x) + __uint_as_float(v[i].z);
                rq += fabsf(__uint_as_float(v[i].y)) + fabsf(__uint_as_float(v[i].w));
            }
            const float2 lp = ln_params(rs, rq, 1.f / 512.f);
            sts64f(s_row + t * 8, lp.x, lp.y);
            if (wl) {
                float c0 = 0.f, c1 = 0.f, c2 = 0.f, c3 = 0.f;
#pragma unroll
                for (int i = 0; i < 8; i++) { c0 += __uint_as_float(u[i].x); c1 += __uint_as_float(u[i].y); c2 += __uint_as_float(u[i].z); c3 += __uint_as_float(u[i].w); }
                sts64f(s_cs + (t >> 6) * 768 + (t & 63) * 16, c0, c1);
                sts64f(s_cs + (t >> 6) * 768 + (t & 63) * 16 + 8, c2, c3);
            }
            bar_sync(3, 128);
            if (t < 96) {
                const float2 a = lds64f(s_cs + t * 8), b = lds64f(s_cs + 768 + t * 8);
                sts64f(s_cs + t * 8, a.x + b.x, a.y + b.y);
            }
        }
        if (t == 0) TS(0, 2);
        __syncwarp();
        bar_arrive(1, 384);
    } else {
        if (warp >= PF_PRE && PF_GAP) {
            while (clock32() - tstart < warp * PF_GAP) {}
            if (lane < 28) asm volatile("prefetch.global.L2 [%0];" ::"l"(pf));
        }
        const int wg = warp >> 2;
        const uint32_t a_lo = desc_lo(sb + wg * 8192, 16), b_lo = desc_lo(sb + 16384, 4096);
        float acc[96];
#pragma unroll
        for (int i = 0; i < 8; i++) {
            const int s = i % G1_ST;
            mbar_wait(s_bar + s * 8, i / G1_ST);
            if (tid == 0) TS(0, 8 + i);
            wg_fence();
#pragma unroll
            for (int kk = 0; kk < 4; kk++) {
                const uint64_t da = desc64(a_lo + ((s * G1_STB + kk * 32) >> 4), SW_HI);
                const uint64_t db = desc64(b_lo + ((s * G1_STB + (kk >> 1) * 12288 + (kk & 1) * 2048) >> 4), SW_HI);
                if (i == 0 && kk == 0) wgmma_ss0_n192<0, 1>(acc, da, db); else wgmma_ss1_n192<0, 1>(acc, da, db);
            }
            wg_commit();
            if (i >= 1 && i <= 3) {
                wg_wait<1>();
                if ((tid & 127) < 2) mbar_arrive_cluster(s_bar + 64 + (i - 1) * 8, tid & 1);
            }
        }
        wg_wait<0>();
        fence_regs(acc);
        if (tid == 0) TS(0, 3);
        bar_sync(1, 384);
        if (tid == 0) TS(0, 4);
        const int g = lane >> 2, q = lane & 3;
        const int r0 = warp * 16 + g;
        const float2 p0 = lds64f(s_row + r0 * 8), p1 = lds64f(s_row + (r0 + 8) * 8);
        const uint32_t stg = sb + (lane >> 4) * 2048 + (warp * 16 + (lane & 15)) * 16;
        uint4 prev;
        bf16* gprev;
#pragma unroll
        for (int th = 0; th < 3; th++) {
            const int tg = nb * 3 + th;
            const int part = tg >> 3;
            const float sc = part == 0 ? 0.25f * 1.4426950408889634f : 1.f;
            const float a0 = p0.x * sc, b0 = p0.y * sc, a1 = p1.x * sc, b1 = p1.y * sc;
            uint32_t mx = 0;
#pragma unroll
            for (int jj = 0; jj < 8; jj += 2) {
                uint32_t v[4];
#pragma unroll
                for (int e = 0; e < 2; e++) {
                    const int j = th * 8 + jj + e;
                    const float2 c2 = lds64f(s_cs + (j * 8 + q * 2) * 4);
                    v[2 * e] = pack_bf16(fmaf(b0, c2.x, acc[4 * j] * a0), fmaf(b0, c2.y, acc[4 * j + 1] * a0));
                    v[2 * e + 1] = pack_bf16(fmaf(b1, c2.x, acc[4 * j + 2] * a1), fmaf(b1, c2.y, acc[4 * j + 3] * a1));
                    asm("max.NaN.xorsign.abs.bf16x2 %0, %0, %1;" : "+r"(mx) : "r"(v[2 * e]));
                    asm("max.NaN.xorsign.abs.bf16x2 %0, %0, %1;" : "+r"(mx) : "r"(v[2 * e + 1]));
                }
                stsm4(stg + (th * 8 + jj) * 2048, v[0], v[1], v[2], v[3]);
                if (th | jj) *(uint4*)gprev = prev;
                __syncwarp();
                prev = lds128(stg + (th * 8 + jj) * 2048);
                gprev = g_qkv + (size_t)((((tg & 7) * 4 + jj / 2) * 16 + mb) * 6 + (part == 0 ? 4 : (part - 1) * 2) + (lane >> 4)) * 1024 + (warp * 16 + (lane & 15)) * 8;
                if (th == 2 && jj == 6) *(uint4*)gprev = prev;
            }
            const int slot = part == 0 ? 4 : (part - 1) * 2;
            if (STG_FINE) {
            } else if ((STG_MASK >> th) & 1) {
                __syncwarp();
                bf16* gp = g_qkv + (size_t)((((tg & 7) * 4) * 16 + mb) * 6 + slot + (lane >> 4)) * 1024 + (warp * 16 + (lane & 15)) * 8;
#pragma unroll
                for (int i = 0; i < 4; i++) *(uint4*)(gp + i * 16 * 6144) = lds128(stg + (th * 8 + i * 2) * 2048);
            } else {
                fence_proxy_async();
                bar_sync(2, 256);
                if (lane == 0 && warp < 4) {
                    bulk_store(g_qkv + (size_t)((((tg & 7) * 4 + warp) * 16 + mb) * 6 + slot) * 1024, sb + (th * 8 + warp * 2) * 2048, 4096);
                    bulk_commit();
                }
            }
            if (part == 1) {
                uint32_t m = max(mx & 0x7FFFu, (mx >> 16) & 0x7FFFu);
                m = __reduce_max_sync(~0u, m);
                if (lane == 0) g_kmax[(tg - 8) * 128 + mb * 8 + warp] = m;
            }
        }
        if (tid == 0) TS(0, 5);
        if (lane == 0 && warp < 4) bulk_wait_read();
        if (tid == 0) TS(0, 6);
    }
}

constexpr int AT_CH = 10240;
constexpr int AT_SMEM = 16 * AT_CH + 16384 + 256 + 512 + 1024;

__device__ __forceinline__ uint32_t exp2_pair_fma(float x0, float x1, uint32_t mant) {
    const float C = 12582912.f + 126.f * 128.f - 22.f;
    uint32_t u0 = __float_as_uint(fmaf(x0, 128.f, C)), u1 = __float_as_uint(fmaf(x1, 128.f, C));
    uint32_t L = __byte_perm(u0, u1, 0x5410);
    uint32_t w, ke, a, p;
    asm("lop3.b32 %0, %1, %2, 0x3F803F80, 0xEA;" : "=r"(w) : "r"(L), "r"(mant));
    asm("lop3.b32 %0, %1, %2, 0x00450045, 0xBA;" : "=r"(ke) : "r"(L), "r"(mant));
    asm("fma.rn.bf16x2 %0, %1, %2, %3;" : "=r"(a) : "r"(w), "r"(0x3F423F42u), "r"(0xBD1BBD1Bu));
    asm("fma.rn.bf16x2 %0, %1, %2, %3;" : "=r"(p) : "r"(L), "r"(a), "r"(ke));
    return p;
}
__device__ __forceinline__ uint32_t exp2_pair_mufu(float x0, float x1) { return pack_bf16(ex2f(x0), ex2f(x1)); }

#define P_EARLY 1
#define P_STG 0
#define Z_FAST 0
#define Z_H9 0
#define Z_PACE 2
#define P_PACE 3
#define STAG 0
#define AT_IN 0
#define O_T 1
#define AT_ORD 4
#define AT_T0 416
#define AT_T1 256
#define AT_T2 384
#define MUFU_MASK 0x94949494u
constexpr uint32_t QK_HI = 128 >> 4, PV_HI = 2048 >> 4;
constexpr uint32_t PV_OFF = (4096 >> 4) + ((128u >> 4) << 16) - ((2048u >> 4) << 16);

__device__ __forceinline__ void store_o(uint32_t* dst, const float (&o)[12]) {
    const float i0 = __fdividef(1.f, o[8]), i1 = __fdividef(1.f, o[10]);
    uint32_t v0 = pack_bf16(o[0] * i0, o[1] * i0), v1 = pack_bf16(o[4] * i0, o[5] * i0), v2 = pack_bf16(o[2] * i1, o[3] * i1), v3 = pack_bf16(o[6] * i1, o[7] * i1);
    const bool b0 = threadIdx.x & 1, b1 = threadIdx.x & 2;
    uint32_t t;
    t = __shfl_xor_sync(~0u, b0 ? v0 : v1, 1); if (b0) v0 = t; else v1 = t;
    t = __shfl_xor_sync(~0u, b0 ? v2 : v3, 1); if (b0) v2 = t; else v3 = t;
    t = __shfl_xor_sync(~0u, b1 ? v0 : v2, 2); if (b1) v0 = t; else v2 = t;
    t = __shfl_xor_sync(~0u, b1 ? v1 : v3, 2); if (b1) v1 = t; else v3 = t;
    *(uint4*)dst = make_uint4(v0, v1, v2, v3);
}
__device__ __forceinline__ uint32_t check_o(const float (&o)[12]) {
    float a0 = fmaxf(fmaxf(fabsf(o[0]), fabsf(o[1])), fmaxf(fabsf(o[4]), fabsf(o[5])));
    float a1 = fmaxf(fmaxf(fabsf(o[2]), fabsf(o[3])), fmaxf(fabsf(o[6]), fabsf(o[7])));
    const float sum = ((o[0] + o[1]) + (o[2] + o[3])) + ((o[4] + o[5]) + (o[6] + o[7]));
    a0 = fmaxf(a0, __shfl_xor_sync(~0u, a0, 1)); a0 = fmaxf(a0, __shfl_xor_sync(~0u, a0, 2));
    a1 = fmaxf(a1, __shfl_xor_sync(~0u, a1, 1)); a1 = fmaxf(a1, __shfl_xor_sync(~0u, a1, 2));
    return !(fminf(a0, a1) >= 8.0779e-28f  ) || !(fabsf(sum) < 1e38f);
}
__global__ void __launch_bounds__(512, 1)
k_attn(const bf16* __restrict__ w_in, const bf16* __restrict__ w_sp, const bf16* __restrict__ w_out, const bf16* __restrict__ wo) {
    extern __shared__ uint8_t smem_raw[];
    const uint32_t sb = (smem_u32(smem_raw) + 1023) & ~1023u;
    const uint32_t s_q = sb + 16 * AT_CH;
    const uint32_t s_bar = s_q + 16384;
    const int tid = threadIdx.x, warp = tid >> 5, lane = tid & 31;
    if (blockIdx.x < 4) {
        if (tid == 0) TS(1, 50);
        if (tid < 8) prefetch_l2(w_out + (blockIdx.x * 8 + tid) * 14336, 28672);
        const int cg = tid % 56, rg = tid / 56;
        float a[8];
#pragma unroll
        for (int i = 0; i < 8; i++) a[i] = 0.f;
        if (rg < 8) {
            const uint4* src = (const uint4*)(w_in + (size_t)rg * 64 * 1792 + blockIdx.x * 448 + cg * 8);
#pragma unroll 16
            for (int r = 0; r < 64; r++) {
                uint4 v = __ldg(src + r * 224);
                a[0] += bf_lo(v.x); a[1] += bf_hi(v.x); a[2] += bf_lo(v.y); a[3] += bf_hi(v.y);
                a[4] += bf_lo(v.z); a[5] += bf_hi(v.z); a[6] += bf_lo(v.w); a[7] += bf_hi(v.w);
            }
            float* sp = (float*)(smem_raw) + rg * 448 + cg * 8;
#pragma unroll
            for (int i = 0; i < 8; i++) sp[i] = a[i];
        }
        __syncthreads();
        if (tid < 448) {
            float s = 0.f;
#pragma unroll
            for (int i = 0; i < 8; i++) s += ((float*)smem_raw)[i * 448 + tid];
            g_cs_in[blockIdx.x * 448 + tid] = s;
        }
        if (tid == 0) TS(1, 51);
#pragma unroll 1
        for (int kb = blockIdx.x; kb < 14; kb += 4) {
            const int c2 = tid & 255, f = c2 / 40, n = (c2 - f * 40) * 2;
            uint32_t v[4][8];
#pragma unroll
            for (int i = 0; i < 4; i++)
#pragma unroll
                for (int e = 0; e < 8; e++) v[i][e] = __ldg((const uint32_t*)w_out + (kb * 64 + (i * 2 + (tid >> 8)) * 8 + e) * 256 + c2);
            if (tid < 7) asm volatile("cp.async.bulk.wait_group.read 0;" ::: "memory");
            __syncthreads();
#pragma unroll
            for (int i = 0; i < 4; i++) {
                const int c = i * 2 + (tid >> 8);
                const uint32_t d = sb + f * 10240 + n * 128;
                asm volatile("st.shared.v4.u32 [%0], {%1,%2,%3,%4};" ::"r"(d + ((c ^ (n & 7)) << 4)), "r"(__byte_perm(v[i][0], v[i][1], 0x5410)),
                             "r"(__byte_perm(v[i][2], v[i][3], 0x5410)), "r"(__byte_perm(v[i][4], v[i][5], 0x5410)), "r"(__byte_perm(v[i][6], v[i][7], 0x5410)) : "memory");
                asm volatile("st.shared.v4.u32 [%0], {%1,%2,%3,%4};" ::"r"(d + 128 + ((c ^ ((n + 1) & 7)) << 4)), "r"(__byte_perm(v[i][0], v[i][1], 0x7632)),
                             "r"(__byte_perm(v[i][2], v[i][3], 0x7632)), "r"(__byte_perm(v[i][4], v[i][5], 0x7632)), "r"(__byte_perm(v[i][6], v[i][7], 0x7632)) : "memory");
            }
            fence_proxy_async();
            __syncthreads();
            if (tid < 7) {
                bulk_store(g_wt + (tid * 14 + kb) * 5120, sb + tid * 10240, tid < 6 ? 10240 : 4096);
                bulk_commit();
            }
        }
        if (tid < 7) bulk_wait0();
        if (tid == 0) TS(1, 52);
        pdl_wait();
        pdl_launch();
        for (int i = blockIdx.x * 512 + tid; i < XP_N / 2; i += 2048) ((uint4*)g_xp)[i] = make_uint4(0, 0, 0, 0);
        if (tid == 0) TS(1, 53);
        return;
    }
    const int bid = blockIdx.x - 4, head = bid >> 2, qb = bid & 3;
    const uint32_t s_km = s_bar + 256;
    if (tid == 0) {
        TS(1, 0);
#pragma unroll
        for (int i = 0; i < 9; i++) mbar_init(s_bar + i * 8, 1);
        fence_mbar_init();
#pragma unroll
        for (int i = 0; i < 9; i++) mbar_expect_tx(s_bar + i * 8, (i < 4 ? 8192 : i == 4 ? 12 * 8192 + 512 : 4096) + (AT_ORD ? (i == 0 ? -4096 : i == 1 ? 4096 : 0) : 0));
    }
    {
        const uint32_t one = 0x3F803F80u;
#pragma unroll
        for (int i = 0; i < 4; i++) {
            int idx = i * 512 + tid;
            asm volatile("st.shared.v4.u32 [%0], {%1,%1,%1,%1};" ::"r"(sb + (idx >> 7) * AT_CH + 8192 + (idx & 127) * 16), "r"(one) : "memory");
        }
        fence_proxy_async();
    }
    __syncthreads();
    const int wg = __shfl_sync(~0u, warp >> 2, 0);
    if (tid == AT_T0) {
        const bf16* hb = g_qkv + (size_t)head * 16 * 6144;
        pdl_wait();
        TS(1, 1);
        bulk_load(sb, hb, 4096, s_bar);
#pragma unroll
        for (int i = 0; i < 4; i++) bulk_load(s_q + i * 4096, hb + (qb * 4 + i) * 6144 + 4096, 4096, s_bar + 40 + i * 8);
        bulk_load(sb + 4096, hb + 2048, 4096, s_bar + 8);
#pragma unroll
        for (int i = 1; i < 4; i++) {
            if (i == AT_ORD) mbar_wait(s_bar + 40, 0);
            bulk_load(sb + i * AT_CH, hb + i * 6144, 8192, s_bar + i * 8);
        }
        pdl_launch();
    }
    if ((tid & 127) == 0) {
        const bf16* hb = g_qkv + (size_t)head * 16 * 6144;
        mbar_wait(s_bar + 40 + wg * 8, 0);
#pragma unroll
        for (int i = 1; i < 4; i++) {
            const int c = i * 4 + wg;
            bulk_load(sb + c * AT_CH, hb + c * 6144, 8192, s_bar + 32);
        }
        if (wg == 3) bulk_load(s_km, g_kmax + (head >> 2) * 128, 512, s_bar + 32);
    }
    __syncwarp();
    mbar_wait(s_bar + 40 + wg * 8, 0);
    if (tid == 0) TS(1, 2);
    uint32_t mant = 0x007F007Fu;
    asm volatile("" : "+r"(mant));
    const uint32_t k_lo = desc_lo(sb, 2048), q_lo = desc_lo(s_q + wg * 4096, 2048);
    uint32_t* dst = (uint32_t*)(g_o + (size_t)(qb * 512 + wg * 128 + (warp & 3) * 16 + (lane >> 2) + (lane & 2) * 4) * 512 + head * 16 + (lane & 1) * 8);
    uint32_t redo = 0;
    {
        float o[12], s[64];
#pragma unroll
        for (int i = 0; i < 12; i++) o[i] = 0.f;
        fence_regs(o);
        mbar_wait(s_bar, 0);
        wg_fence();
        uint64_t dk = desc64(k_lo, QK_HI), dq = desc64(q_lo, QK_HI), dv[8];
#pragma unroll
        for (int i = 0; i < 8; i++) dv[i] = desc64(k_lo + PV_OFF + i * 16, PV_HI);
        wgmma_ss0_n128<0, 0>(s, dq, dk);
        wg_commit();
        wg_wait<0>();
        fence_regs(s);
        uint32_t kstep = AT_CH >> 4;
        int sd = 1;
#pragma unroll 1
        for (int seg = 0; seg < 7; seg++) {
            int n = 1;
            if ((tid & 127) == 0) TS(1, 8 + wg * 8 + seg);
            if (seg < 4) {
                mbar_wait(s_bar + 8 + seg * 8, 0);
                if (seg == 3) n = 12;
            } else if (seg == 4) {
                kstep = (uint32_t)(-15 * (AT_CH >> 4));
                desc_add(dq, 64);
            } else if (seg == 5) {
                kstep = AT_CH >> 4;
                sd = 0;
                store_o(dst, o);
                redo = check_o(o);
                const uint4 km = lds128(s_km + lane * 16);
                const uint32_t mk = __reduce_max_sync(~0u, max(max(km.x, km.y), max(km.z, km.w)));
                const float kmax = __uint_as_float(mk << 16);
                const uint4 a = lds128(s_q + wg * 4096 + (tid & 127) * 16), b = lds128(s_q + wg * 4096 + 2048 + (tid & 127) * 16);
                const uint32_t w[8] = {a.x, a.y, a.z, a.w, b.x, b.y, b.z, b.w};
                float l1 = 0.f;
#pragma unroll
                for (int i = 0; i < 8; i++) l1 += fabsf(bf_lo(w[i])) + fabsf(bf_hi(w[i]));
                if (!(l1 * kmax <= 100.f)) redo = 1;
                if (tid == AT_T2) {
                    prefetch_l2(w_sp + (size_t)bid * 32768, 65536);
                    prefetch_l2(wo + (size_t)bid * 2048, 4096);
                }
                __syncwarp();
            } else {
                sd = 1;
                n = 15;
            }
#pragma unroll 1
            do {
                uint32_t pa[8], pb[16];
#pragma unroll
                for (int j = 0; j < 8; j++)
                    pa[j] = ((MUFU_MASK >> j) & 1) ? exp2_pair_mufu(s[2 * j], s[2 * j + 1]) : exp2_pair_fma(s[2 * j], s[2 * j + 1], mant);
                wg_fence();
                wgmma_rs_n24<1>(o, pa[0], pa[1], pa[2], pa[3], dv[0], sd);
                wgmma_rs1_n24<1>(o, pa[4], pa[5], pa[6], pa[7], dv[1]);
                wg_commit();
#pragma unroll
                for (int j = 8; j < 24; j++)
                    pb[j - 8] = ((MUFU_MASK >> j) & 1) ? exp2_pair_mufu(s[2 * j], s[2 * j + 1]) : exp2_pair_fma(s[2 * j], s[2 * j + 1], mant);
                wg_wait<0>();
#pragma unroll
                for (int j = 24; j < 32; j++)
                    pa[j - 24] = ((MUFU_MASK >> j) & 1) ? exp2_pair_mufu(s[2 * j], s[2 * j + 1]) : exp2_pair_fma(s[2 * j], s[2 * j + 1], mant);
                wg_fence();
#pragma unroll
                for (int kk = 0; kk < 4; kk++) wgmma_rs1_n24<1>(o, pb[4 * kk], pb[4 * kk + 1], pb[4 * kk + 2], pb[4 * kk + 3], dv[2 + kk]);
                wgmma_rs1_n24<1>(o, pa[0], pa[1], pa[2], pa[3], dv[6]);
                wgmma_rs1_n24<1>(o, pa[4], pa[5], pa[6], pa[7], dv[7]);
                desc_add(dk, kstep);
                wgmma_ss0_n128<0, 0>(s, dq, dk);
                wg_commit();
#pragma unroll
                for (int i = 0; i < 8; i++) desc_add(dv[i], kstep);
                wg_wait<0>();
                fence_regs(s);
                fence_regs(o);
            } while (--n);
        }
        store_o(dst + 64 * 256, o);
        redo |= check_o(o);
        uint32_t r;
        asm volatile("{\n.reg .pred p, q;\nsetp.ne.u32 q, %1, 0;\nbarrier.cta.red.or.pred.aligned p, %2, 128, q;\nselp.u32 %0, 1, 0, p;\n}" : "=r"(r) : "r"(redo), "r"(1 + wg) : "memory");
        redo = __any_sync(~0u, r != 0);
    }
    if ((tid & 127) == 0) TS(1, 40 + wg);
    if (redo) {
#pragma unroll 1
        for (int t = 0; t < 2; t++) {
            const uint64_t dq = desc64(q_lo + t * 64, QK_HI);
            float o[12], s[64];
#pragma unroll
            for (int i = 0; i < 12; i++) o[i] = 0.f;
            float m0 = -INFINITY, m1 = -INFINITY;
            uint32_t lo = k_lo;
#pragma unroll 1
            for (int c = 0; c < 16; c++, lo += AT_CH >> 4) {
                wg_fence();
                wgmma_ss0_n128<0, 0>(s, dq, desc64(lo, QK_HI));
                wg_commit();
                wg_wait<0>();
                fence_regs(s);
                float a0 = m0, a1 = m1;
#pragma unroll
                for (int j = 0; j < 16; j++) {
                    a0 = fmaxf(a0, fmaxf(s[4 * j], s[4 * j + 1]));
                    a1 = fmaxf(a1, fmaxf(s[4 * j + 2], s[4 * j + 3]));
                }
                a0 = fmaxf(a0, __shfl_xor_sync(~0u, a0, 1)); a0 = fmaxf(a0, __shfl_xor_sync(~0u, a0, 2));
                a1 = fmaxf(a1, __shfl_xor_sync(~0u, a1, 1)); a1 = fmaxf(a1, __shfl_xor_sync(~0u, a1, 2));
                const float f0 = (m0 == -INFINITY) ? 0.f : ex2f(m0 - a0), f1 = (m1 == -INFINITY) ? 0.f : ex2f(m1 - a1);
                m0 = a0; m1 = a1;
                const float b0 = (a0 == -INFINITY) ? 0.f : a0, b1 = (a1 == -INFINITY) ? 0.f : a1;
#pragma unroll
                for (int j = 0; j < 3; j++) { o[4 * j] *= f0; o[4 * j + 1] *= f0; o[4 * j + 2] *= f1; o[4 * j + 3] *= f1; }
                fence_regs(o);
#pragma unroll
                for (int hh = 0; hh < 2; hh++) {
                    uint32_t p[16];
#pragma unroll
                    for (int j = 0; j < 8; j++) {
                        p[2 * j] = pack_bf16(ex2f(s[32 * hh + 4 * j] - b0), ex2f(s[32 * hh + 4 * j + 1] - b0));
                        p[2 * j + 1] = pack_bf16(ex2f(s[32 * hh + 4 * j + 2] - b1), ex2f(s[32 * hh + 4 * j + 3] - b1));
                    }
                    wg_fence();
#pragma unroll
                    for (int kk = 0; kk < 4; kk++)
                        wgmma_rs1_n24<1>(o, p[4 * kk], p[4 * kk + 1], p[4 * kk + 2], p[4 * kk + 3], desc64(lo + PV_OFF + (hh * 4 + kk) * 16, PV_HI));
                    wg_commit();
                    wg_wait<0>();
                    fence_regs(o);
                }
            }
            store_o(dst + t * 64 * 256, o);
        }
    }
}

#define PW_PRE 4
#define PW_DIV 2
template <int NKB, int NST, bool STATS>
__global__ void __cluster_dims__(2, 1, 1) __launch_bounds__(288, 1)
k_proj(const __grid_constant__ CUtensorMap tm_a, const __grid_constant__ CUtensorMap tm_w, const __grid_constant__ CUtensorMap tm_res,
       const __grid_constant__ CUtensorMap tm_out) {
    extern __shared__ uint8_t smem_raw[];
    const uint32_t sb = (smem_u32(smem_raw) + 1023) & ~1023u;
    const uint32_t s_w = sb + NST * 16384;
    const uint32_t s_r = s_w + NKB * 8192;
    const uint32_t s_bar = s_r + 16384;
    const int tid = threadIdx.x, warp = __shfl_sync(~0u, tid >> 5, 0), lane = tid & 31;
    const uint32_t rank = cluster_rank();
    const int mb = blockIdx.x >> 3, nb = blockIdx.x & 7;
    constexpr int KI = STATS ? 2 : 5;
    if (tid == 256) {
        TS(KI, 0);
        pdl_launch();
        prefetch_tmap(&tm_w); prefetch_tmap(&tm_res); prefetch_tmap(&tm_a); prefetch_tmap(&tm_out);
#pragma unroll
        for (int i = 0; i < NST; i++) { mbar_init(s_bar + i * 8, 1); mbar_init(s_bar + 64 + i * 8, 4); }
#pragma unroll
        for (int i = 0; i < NKB / 2; i++) mbar_init(s_bar + 128 + i * 8, 1);
        mbar_init(s_bar + 192, 1);
        fence_mbar_init();
#pragma unroll
        for (int i = 0; i < NKB / 2; i++) {
            mbar_expect_tx(s_bar + 128 + i * 8, 16384);
            if (i < PW_PRE) tma_2d(s_w + i * 16384, &tm_w, s_bar + 128 + i * 8, nb * 64, i * 128);
        }
        mbar_expect_tx(s_bar + 192, 16384);
#pragma unroll
        for (int i = 0; i < NST; i++) mbar_expect_tx(s_bar + i * 8, 16384);
    }
    __syncwarp();
    cluster_sync_relaxed();
    if (warp == 8) {
        if (lane == 0) {
            TS(KI, 1);
            pdl_wait();
            TS(KI, 2);
#pragma unroll
            for (int kb = 0; kb < NKB; kb++) {
                const int s = kb % NST;
                if (kb >= NST) {
                    mbar_wait(s_bar + 64 + s * 8, (kb / NST - 1) & 1);
                    mbar_expect_tx(s_bar + s * 8, 16384);
                }
                if (P_PACE && NKB == NST && kb >= P_PACE) mbar_wait(s_bar + (kb - P_PACE) * 8, 0);
                tma_2d_mc(sb + s * 16384 + rank * 8192, &tm_a, s_bar + s * 8, kb * 64, mb * 128 + rank * 64, (uint16_t)3);
                const int i = PW_PRE + kb / PW_DIV;
                if (kb % PW_DIV == PW_DIV - 1 && i < NKB / 2) tma_2d(s_w + i * 16384, &tm_w, s_bar + 128 + i * 8, nb * 64, i * 128);
                if (kb == (NKB > NST ? NST + 1 : NKB - 1)) tma_2d(s_r, &tm_res, s_bar + 192, nb * 64, mb * 128);
            }
        }
    } else {
        const int wg = warp >> 2, q = lane & 3;
        const uint32_t a_lo = desc_lo(sb + wg * 8192, 16), b_lo = desc_lo(s_w, 8192);
        float acc[32];
#pragma unroll
        for (int kb = 0; kb < NKB; kb++) {
            const int s = kb % NST;
            if (!(kb & 1)) mbar_wait(s_bar + 128 + kb * 4, 0);
            mbar_wait(s_bar + s * 8, (kb / NST) & 1);
            if (tid == 0) TS(KI, 8 + kb);
            wg_fence();
#pragma unroll
            for (int kk = 0; kk < 4; kk++) {
                const uint64_t da = desc64(a_lo + ((s * 16384 + kk * 32) >> 4), SW_HI), db = desc64(b_lo + ((kb * 8192 + kk * 2048) >> 4), SW_HI);
                if (kb == 0 && kk == 0) wgmma_ss0_n64<0, 1>(acc, da, db); else wgmma_ss1_n64<0, 1>(acc, da, db);
            }
            wg_commit();
            if (NKB > NST && kb >= 1 && kb - 1 + NST < NKB) {
                wg_wait<1>();
                if ((tid & 127) < 2) mbar_arrive_cluster(s_bar + 64 + ((kb - 1) % NST) * 8, tid & 1);
            }
        }
        const int row = warp * 16 + (lane & 15);
        const uint32_t stg = s_r + row * 128;
        uint32_t v[16];
        mbar_wait(s_bar + 192, 0);
#pragma unroll
        for (int j = 0; j < 8; j += 2) ldsm4(stg + (((j + (lane >> 4)) ^ (row & 7)) << 4), v[2 * j], v[2 * j + 1], v[2 * j + 2], v[2 * j + 3]);
        wg_wait<0>();
        fence_regs(acc);
        if (tid == 0) TS(KI, 3);
        float s0 = 0.f, q0 = 0.f, s1 = 0.f, q1 = 0.f;
#pragma unroll
        for (int j = 0; j < 8; j++) {
            v[2 * j] = pack_bf16(acc[4 * j] + bf_lo(v[2 * j]), acc[4 * j + 1] + bf_hi(v[2 * j]));
            v[2 * j + 1] = pack_bf16(acc[4 * j + 2] + bf_lo(v[2 * j + 1]), acc[4 * j + 3] + bf_hi(v[2 * j + 1]));
        }
#pragma unroll
        for (int j = 0; j < 8; j += 2) stsm4(stg + (((j + (lane >> 4)) ^ (row & 7)) << 4), v[2 * j], v[2 * j + 1], v[2 * j + 2], v[2 * j + 3]);
        fence_proxy_async();
        __syncwarp();
        if (lane == 0) {
            tma_store_2d(&tm_out, s_r + warp * 2048, nb * 64, mb * 128 + warp * 16);
            bulk_commit();
        }
        if (STATS) {
#pragma unroll
            for (int j = 0; j < 8; j++) {
                float a = bf_lo(v[2 * j]), b = bf_hi(v[2 * j]), c = bf_lo(v[2 * j + 1]), d = bf_hi(v[2 * j + 1]);
                s0 += a + b; q0 = fmaf(a, a, fmaf(b, b, q0)); s1 += c + d; q1 = fmaf(c, c, fmaf(d, d, q1));
            }
            s0 = quad_sum(s0); q0 = quad_sum(q0); s1 = quad_sum(s1); q1 = quad_sum(q1);
            if (q < 2) g_hpart[(mb * 128 + warp * 16 + (lane >> 2) + q * 8) * 8 + nb] = q ? make_float2(s1, q1) : make_float2(s0, q0);
        }
        if (tid == 0) TS(KI, 4);
        if (lane == 0) bulk_wait_read();
        if (tid == 0) TS(KI, 5);
    }
}

struct TileMap { int tblk, ftile, tpart, fpart; uint16_t fmask, tmask; bool quad; };
__device__ __forceinline__ TileMap tile_map() {
    TileMap m;
    const int c = blockIdx.x >> 2, r = cluster_rank();
    m.quad = c >= 24;
    const int ti = r & 1, fi = r >> 1;
    m.tblk = m.quad ? (c - 24) * 4 + r : (c / 3) * 2 + ti;
    m.ftile = m.quad ? 6 : (c % 3) * 2 + fi;
    m.fmask = m.quad ? 15 : 3 << (2 * fi);
    m.tmask = m.quad ? 1 << r : 5 << ti;
    m.fpart = m.quad ? r : 2 * ti;
    m.tpart = m.quad ? 0 : fi;
    return m;
}
__device__ __forceinline__ void load_T(const TileMap& m, uint32_t dst, uint32_t bar, const CUtensorMap* tm, int k0) {
    tma_2d_mc(dst + m.tpart * 8192, tm, bar, k0, m.tblk * 128 + m.tpart * 64, m.tmask);
}
__device__ __forceinline__ void load_F(const TileMap& m, uint32_t dst, uint32_t bar, const CUtensorMap* tm, int k0, int fcol0) {
    tma_2d_mc(dst + m.fpart * 4096, tm, bar, fcol0 + (m.fpart >> 1) * 64, k0 + (m.fpart & 1) * 32, m.fmask);
}
struct Maps4 { CUtensorMap h[2], win[2], wsp[2], z2[2], u[2], out; };

constexpr int G4_SMEM = 14 * 16384 + 1024 + 512 + 1024;
#define Z_POLL 11
#define Z_NORM 13
#define Z_R 4
#define Z_INL 0
#define POLL3 0
#define W_PRE 3
__device__ __forceinline__ uint32_t ld_vol32(const uint32_t* p) { uint32_t v; asm volatile("ld.volatile.global.u32 %0, [%1];" : "=r"(v) : "l"(p) : "memory"); return v; }
__device__ __forceinline__ void red_or(uint32_t* p, uint32_t v) { asm volatile("red.relaxed.gpu.global.or.b32 [%0], %1;" ::"l"(p), "r"(v) : "memory"); }
__device__ __forceinline__ void dsmem_copy(uint32_t dst, uint32_t src, uint32_t bytes, uint32_t bar, uint32_t cta) {
    asm volatile("{\n.reg .b32 rd, rb;\nmapa.shared::cluster.u32 rd, %0, %4;\nmapa.shared::cluster.u32 rb, %3, %4;\n"
                 "cp.async.bulk.shared::cluster.shared::cta.mbarrier::complete_tx::bytes [rd], [%1], %2, [rb];\n}"
                 ::"r"(dst), "r"(src), "r"(bytes), "r"(bar), "r"(cta) : "memory");
}
__device__ __forceinline__ void bulk_load_mc(uint32_t dst, const void* src, uint32_t bytes, uint32_t bar, uint16_t mask) {
    asm volatile("cp.async.bulk.shared::cluster.global.mbarrier::complete_tx::bytes.multicast::cluster [%0], [%1], %2, [%3], %4;"
                 ::"r"(dst), "l"(src), "r"(bytes), "r"(bar), "h"(mask) : "memory");
}
__device__ __forceinline__ void mma_kb(float (&acc)[64], const uint64_t (&da)[4], const uint64_t (&db)[4], int sd) {
    wg_fence();
    wgmma_ss_n128<0, 1>(acc, da[0], db[0], sd);
#pragma unroll
    for (int kk = 1; kk < 4; kk++) wgmma_ss1_n128<0, 1>(acc, da[kk], db[kk]);
    wg_commit();
}
__device__ __forceinline__ void desc_add4(uint64_t (&d)[4], uint32_t inc) {
#pragma unroll
    for (int kk = 0; kk < 4; kk++) desc_add(d[kk], inc);
}
__device__ __forceinline__ float gelu_h(float hy) {
    const float in = hy * fmaf(hy * hy, 8.f * 0.7978845608028654f * 0.044715f, 2.f * 0.7978845608028654f);
    return fmaf(hy, tanhf_(in), hy);
}
__global__ void __cluster_dims__(4, 1, 1) __launch_bounds__(320, 1)
k_zg(const __grid_constant__ Maps4 tm, const bf16* __restrict__ b_sp) {
    extern __shared__ uint8_t smem_raw[];
    const uint32_t sb = (smem_u32(smem_raw) + 1023) & ~1023u;
    const uint32_t s_b = sb + 8 * 16384;
    const uint32_t s_cs = sb + 14 * 16384;
    const uint32_t s_bar = s_cs + 1024;
    const int tid = threadIdx.x, warp = __shfl_sync(~0u, tid >> 5, 0), lane = tid & 31;
    const TileMap m = tile_map();
    if (lane == 0) {
        if (warp < 6) {
            const int cnt = warp == 5 ? 4 : warp == 1 || warp == 4 ? 8 : 1;
#pragma unroll
            for (int i = 0; i < 8; i++) mbar_init(s_bar + warp * 64 + i * 8, cnt);
            fence_mbar_init();
            if (cnt == 1) {
#pragma unroll
                for (int i = 0; i < 8; i++) mbar_expect_tx(s_bar + warp * 64 + i * 8, i >= 2 && warp == 3 ? 32768 : 16384);
            }
        } else if (warp == 8) {
            TS(3, 0);
            prefetch_tmap(&tm.win[blockIdx.x >= 96]); prefetch_tmap(&tm.h[blockIdx.x >= 96]);
        }
    }
    __syncwarp();
    cluster_sync_relaxed();
    uint32_t* flag = (uint32_t*)(g_xp + XP_F) + m.ftile * 32;
    uint32_t* uflag = (uint32_t*)(g_xp + XP_U) + m.tblk * 32;
    if (tid == 256) TS(3, 25);
    if (warp == 8) {
        if (lane == 0) {
            const CUtensorMap *t_h = &tm.h[m.quad], *t_win = &tm.win[m.quad], *t_wsp = &tm.wsp[m.quad];
#pragma unroll
            for (int i = 0; i < W_PRE; i++) load_F(m, s_b + (i + 2) % 6 * 16384, s_bar + i * 8, t_win, i * 64, 896 + m.ftile * 128);
            TS(3, 1);
            pdl_wait();
            TS(3, 2);
#pragma unroll
            for (int i = 0; i < 8; i++) {
                if (Z_PACE && i >= Z_PACE) mbar_wait(s_bar + 128 + (i - Z_PACE) * 8, 0);
                if (i >= W_PRE && i < 6) load_F(m, s_b + (i + 2) % 6 * 16384, s_bar + i * 8, t_win, i * 64, 896 + m.ftile * 128);
                if (i >= Z_H9) load_T(m, sb + i * 16384, s_bar + 128 + i * 8, t_h, i * 64);
            }
            prefetch_tmap(t_wsp); prefetch_tmap(&tm.z2[0]); prefetch_tmap(&tm.z2[1]);
#pragma unroll 1
            for (int i = 6, s = 0; i < 16; i++, s = s == 5 ? 0 : s + 1) {
                mbar_wait(s_bar + 64 + s * 8, i >= 12);
                mbar_expect_tx(s_bar + s * 8, 16384);
                load_F(m, s_b + (s < 4 ? s + 2 : s - 4) * 16384, s_bar + s * 8, t_win, (i & 7) * 64, (i < 8 ? 896 : 0) + m.ftile * 128);
            }
            const int kp = (m.tblk >> 1) * 4;
#pragma unroll 1
            for (int i = 0; i < 6; i++) {
                mbar_wait(s_bar + 256 + i * 8, 0);
                TS(4, 40 + i);
                load_T(m, s_b + i * 16384, s_bar + 192 + i * 8, t_wsp, (i < 4 ? (m.tblk * 2) ^ i : m.quad ? kp ^ i : (kp + i) & 31) * 64);
            }
            uint32_t ready = 0, ph = 0;
            const uint32_t r = cluster_rank();
#pragma unroll 1
            for (int i = 4, s = 4; i < 32; i++) {
                const bool q4 = m.quad && i >= 8;
                const int kb = q4 ? ((kp & ~7) + i) & 31 : m.quad ? kp ^ i : (kp + i) & 31;
                const uint32_t need = (1u << kb) | (15u << kp);
                for (int n = 0; (ready & need) != need; n++) {
                    ready = ld_vol32(flag);
                    if (n > 0x400000) __trap();
                }
                if (i < 16) TS(4, 46 + i);
                if (i >= 6) {
                    mbar_wait(s_bar + 256 + s * 8, ph);
                    mbar_expect_tx(s_bar + 192 + s * 8, 32768);
                    load_T(m, s_b + s * 16384, s_bar + 192 + s * 8, t_wsp, kb * 64);
                }
                const int fp = q4 ? r : (r & 1) * 2;
                tma_2d_mc(sb + s * 16384 + fp * 4096, &tm.z2[q4], s_bar + 192 + s * 8, m.ftile * 128 + (fp >> 1) * 64, kb * 64 + (fp & 1) * 32,
                          (uint16_t)(q4 ? 15 : 3 << (r & 2)));
                if (++s == 6) { s = 0; ph ^= 1; }
            }
            prefetch_tmap(&tm.u[m.quad]); prefetch_tmap(&tm.h[1]);
            const int nl = m.quad ? 2 : 4, k0 = (m.ftile & 6) * 2;
            const uint32_t wsz = m.quad ? 2560 : 5120, woff = m.fpart * 2560;
            const char* wsrc = (const char*)g_wt + m.ftile * 143360 + woff;
#pragma unroll 1
            for (int j = 0, s = 2; j < 6; j++, s = s == 5 ? 0 : s + 1) {
                const int kb = j < nl ? (m.ftile * 2) ^ j : (k0 + j) % 14;
                mbar_wait(s_bar + 256 + s * 8, j < 4);
                mbar_expect_tx(s_bar + 192 + s * 8, 26624);
                bulk_load_mc(s_b + s * 16384 + woff, wsrc + kb * 10240, wsz, s_bar + 192 + s * 8, m.fmask);
                if (j < 2) tma_2d(sb + s * 16384, &tm.h[1], s_bar + 192 + s * 8, m.ftile * 80 + j * 64, m.tblk * 128);
            }
            ready = 0;
#pragma unroll 1
            for (int j = nl, s = (2 + nl) % 6; j < 14; j++, s = s == 5 ? 0 : s + 1) {
                const int kb = (k0 + j) % 14;
                const uint32_t need = (m.quad ? 3u : 1u << m.tpart) << (kb & 14);
                if (j >= 6) {
                    mbar_wait(s_bar + 256 + s * 8, j >= 10);
                    mbar_expect_tx(s_bar + 192 + s * 8, 26624);
                    bulk_load_mc(s_b + s * 16384 + woff, wsrc + kb * 10240, wsz, s_bar + 192 + s * 8, m.fmask);
                }
                for (int n = 0; (ready & need) != need; n++) {
                    ready = ld_vol32(uflag);
                    if (n > 0x400000) __trap();
                }
                TS(5, 40 + j);
                load_T(m, sb + s * 16384, s_bar + 192 + s * 8, &tm.u[m.quad], kb * 64);
            }
        }
    } else if (warp == 9) {
        if (lane == 0) {
            prefetch_tmap(&tm.z2[0]); prefetch_tmap(&tm.u[0]); prefetch_tmap(&tm.out);
            const uint32_t peer = cluster_rank() ^ 1;
#pragma unroll
            for (int w = 0; w < 2; w++) {
                mbar_wait(s_bar + 320 + w * 8, 0);
                tma_store_2d(&tm.z2[0], sb + w * 16384, m.ftile * 128, m.tblk * 128 + w * 64);
                tma_store_2d(&tm.z2[0], sb + w * 16384 + 8192, m.ftile * 128 + 64, m.tblk * 128 + w * 64);
                bulk_commit();
            }
            TS(3, 4);
#pragma unroll
            for (int w = 0; w < 2; w++) {
                mbar_wait(s_bar + 256 + w * 8, 0);
                dsmem_copy(sb + (2 + w) * 16384, sb + w * 16384, 16384, s_bar + 192 + (2 + w) * 8, peer);
            }
            asm volatile("cp.async.bulk.wait_group 1;" ::: "memory");
            red_or(flag, 1u << (m.tblk * 2));
            bulk_wait0();
            red_or(flag, 2u << (m.tblk * 2));
            TS(3, 5);
#pragma unroll
            for (int w = 0; w < 2; w++) {
                mbar_wait(s_bar + 320 + w * 8, 1);
                tma_store_2d(&tm.u[0], sb + 6 * 16384 + w * 8192, m.ftile * 128, m.tblk * 128 + w * 64);
                tma_store_2d(&tm.u[0], sb + 7 * 16384 + w * 8192, m.ftile * 128 + 64, m.tblk * 128 + w * 64);
                bulk_commit();
            }
            TS(4, 4);
            if (!m.quad) {
#pragma unroll
                for (int w = 0; w < 2; w++) {
                    mbar_wait(s_bar + 256 + (4 + w) * 8, 1);
                    dsmem_copy(sb + (4 + w) * 16384, sb + (6 + w) * 16384, 16384, s_bar + 192 + (4 + w) * 8, peer ^ 3);
                }
            }
            asm volatile("cp.async.bulk.wait_group 1;" ::: "memory");
            red_or(uflag, 1u << (m.ftile * 2));
            bulk_wait0();
            red_or(uflag, 2u << (m.ftile * 2));
            TS(4, 5);
        }
    } else {
        const int wg = warp >> 2, q = lane & 3;
        const int r0 = m.tblk * 128 + warp * 16 + (lane >> 2);
        float b0 = __bfloat162float(b_sp[r0]), b1 = __bfloat162float(b_sp[r0 + 8]);
        asm volatile("" : "+f"(b0), "+f"(b1));
        pdl_wait();
        const float c_in = __ldcg(g_cs_in + (tid < 128 ? 896 : -128) + m.ftile * 128 + tid);
        const float4 h0 = __ldcg((const float4*)(g_hpart + r0 * 8) + q), h1 = __ldcg((const float4*)(g_hpart + (r0 + 8) * 8) + q);
        asm volatile("st.shared.f32 [%0], %1;" ::"r"(s_cs + tid * 4), "f"(c_in) : "memory");
        const int row = warp * 16 + (lane & 15);
        const bool rel = (tid & 127) < 4;
        uint64_t da[4], db[4];
#pragma unroll
        for (int kk = 0; kk < 4; kk++) {
            da[kk] = desc64(desc_lo(sb + wg * 8192 + kk * 32, 16), SW_HI);
            db[kk] = desc64(desc_lo(s_b + 2 * 16384 + kk * 2048, 8192), SW_HI);
        }
        float z2[64], acc[64];
#pragma unroll
        for (int i = 0; i < 64; i++) z2[i] = 0.f;
        fence_regs(z2);
        {
            int s = 0, sp = 0;
#pragma unroll 1
            for (int i = 0; i < 8; i++) {
                mbar_wait(s_bar + 128 + i * 8, 0);
                mbar_wait(s_bar + s * 8, i >= 6);
                if (tid == 0) TS(3, 8 + i);
                mma_kb(z2, da, db, i);
                desc_add4(da, i == 7 ? -7 * 1024 : 1024);
                desc_add4(db, s == 3 ? -5 * 1024 : 1024);
                wg_wait<1>();
                if (rel && i) mbar_arrive_cluster(s_bar + 64 + sp * 8, tid & 3);
                sp = s;
                s = s == 5 ? 0 : s + 1;
            }
        }
        float2 p0 = ln_params(quad_sum(h0.x + h0.z), quad_sum(h0.y + h0.w), 1.f / 512.f);
        float2 p1 = ln_params(quad_sum(h1.x + h1.z), quad_sum(h1.y + h1.w), 1.f / 512.f);
        p0.x *= 0.5f; p0.y *= 0.5f; p1.x *= 0.5f; p1.y *= 0.5f;
        bar_sync(1, 256);
        float s0 = 0.f, q0 = 0.f, s1 = 0.f, q1 = 0.f;
        const uint2* zp = g_xp + XP_Z + r0 * 8 + 2 * q;
        uint4 e0, e1, f0, f1;
#pragma unroll
        for (int i = 8; i < 16; i++) {
            if (i >= 10 && i != Z_NORM + 1) {
                wg_wait<1>();
                if (rel) mbar_arrive_cluster(i < 12 ? s_bar + 64 + (i - 2) % 6 * 8 : s_bar + 256 + (i - 12) * 8, tid & 3);
            }
            mbar_wait(s_bar + i % 6 * 8, i < 12);
            if (tid == 0) TS(3, 8 + i);
            wg_fence();
#pragma unroll
            for (int kk = 0; kk < 4; kk++) {
                const int h = (i - 8) * 4 + kk;
                if (h == 0) {
                    wgmma_ss0_n128<0, 1>(acc, da[0], db[0]);
                    wg_commit();
                    wg_wait<1>();
                    if (rel) mbar_arrive_cluster(s_bar + 64 + 1 * 8, tid & 3);
                    fence_regs(z2);
                } else {
                    wgmma_ss1_n128<0, 1>(acc, da[kk], db[kk]);
                }
                if (kk == 3) wg_commit();
#pragma unroll
                for (int j = h * Z_R; j < (h + 1) * Z_R && j < 16; j++) {
                    const float2 c2 = lds64f(s_cs + (j * 8 + q * 2) * 4);
                    const float a = gelu_h(fmaf(p0.y, c2.x, z2[4 * j] * p0.x)), b = gelu_h(fmaf(p0.y, c2.y, z2[4 * j + 1] * p0.x));
                    const float c = gelu_h(fmaf(p1.y, c2.x, z2[4 * j + 2] * p1.x)), d = gelu_h(fmaf(p1.y, c2.y, z2[4 * j + 3] * p1.x));
                    z2[4 * j] = a; z2[4 * j + 1] = b; z2[4 * j + 2] = c; z2[4 * j + 3] = d;
                    s0 += a + b; q0 = fmaf(a, a, fmaf(b, b, q0)); s1 += c + d; q1 = fmaf(c, c, fmaf(d, d, q1));
                    asm volatile("" : "+f"(z2[4 * j]), "+f"(z2[4 * j + 1]), "+f"(z2[4 * j + 2]), "+f"(z2[4 * j + 3]));
                    asm volatile("" : "+f"(s0), "+f"(q0), "+f"(s1), "+f"(q1));
                    if (j == 15) {
                        s0 = quad_sum(s0); q0 = quad_sum(q0); s1 = quad_sum(s1); q1 = quad_sum(q1);
                        if (q < 2) st_vol64(g_xp + XP_Z + (r0 + q * 8) * 8 + m.ftile, __float_as_uint(q ? s1 : s0), __float_as_uint(q ? q1 : q0) | 0x80000000u);
                        if (tid == 0) TS(3, 6);
                    }
                }
            }
            desc_add4(da, 1024);
            desc_add4(db, i == 15 ? -13 * 1024 : i == 9 ? -5 * 1024 : 1024);
            if (i == Z_POLL) { e0 = ld_vol128(zp); e1 = ld_vol128(zp + 64); }
            if (i == Z_POLL + 1) { f0 = ld_vol128(zp); f1 = ld_vol128(zp + 64); }
            if (i == Z_NORM) {
                wg_wait<1>();
                if (rel) mbar_arrive_cluster(s_bar + 256 + (i - 11) * 8, tid & 3);
                for (int n = 0;; n++) {
                    if (q == 3) { e0.z = 0; e0.w = 0x80000000u; e1.z = 0; e1.w = 0x80000000u; }
                    if (__all_sync(~0u, (e0.y & e0.w & e1.y & e1.w) >> 31)) break;
                    if (n > 0x400000) __trap();
                    e0 = f0; e1 = f1;
                    f0 = ld_vol128(zp); f1 = ld_vol128(zp + 64);
                }
                const float2 n0 = ln_params(quad_sum(__uint_as_float(e0.x) + __uint_as_float(e0.z)), quad_sum(fabsf(__uint_as_float(e0.y)) + fabsf(__uint_as_float(e0.w))), 1.f / 896.f);
                const float2 n1 = ln_params(quad_sum(__uint_as_float(e1.x) + __uint_as_float(e1.z)), quad_sum(fabsf(__uint_as_float(e1.y)) + fabsf(__uint_as_float(e1.w))), 1.f / 896.f);
                if (tid == 0) TS(3, 7);
                mbar_wait(s_bar + 64 + (2 + wg) * 8, 1);
                const uint32_t stg = sb + wg * 16384 + (row & 63) * 128;
#pragma unroll
                for (int j = 0; j < 16; j += 2) {
                    uint32_t v[4];
#pragma unroll
                    for (int e = 0; e < 2; e++) {
                        const int jj = j + e;
                        v[2 * e] = pack_bf16(fmaf(z2[4 * jj], n0.x, n0.y), fmaf(z2[4 * jj + 1], n0.x, n0.y));
                        v[2 * e + 1] = pack_bf16(fmaf(z2[4 * jj + 2], n1.x, n1.y), fmaf(z2[4 * jj + 3], n1.x, n1.y));
                    }
                    stsm4(stg + (j >> 3) * 8192 + ((((j & 7) + (lane >> 4)) ^ (row & 7)) << 4), v[0], v[1], v[2], v[3]);
                }
                fence_proxy_async();
                __syncwarp();
                if (lane == 0) mbar_arrive(s_bar + 320 + wg * 8);
            }
        }
        uint32_t z1[32];
#pragma unroll
        for (int i = 0; i < 4; i++) {
            if (i != 1) {
                if (i) mbar_wait(s_bar + 192 + i * 8, 0);
                wg_wait<1>();
                if (rel) mbar_arrive_cluster(s_bar + 256 + (i + 4) % 6 * 8, tid & 3);
            }
            if (i < 2) { mbar_wait(s_bar + 192 + i * 8, 0); mbar_wait(s_bar + 320 + i * 8, 0); }
            if (tid == 0) TS(4, 8 + i);
            wg_fence();
#pragma unroll
            for (int kk = 0; kk < 4; kk++) {
                const int j = i * 4 + kk;
                if (j == 0) {
                    wgmma_ss0_n128<0, 1>(z2, da[0], db[0]);
                    wg_commit();
                    wg_wait<1>();
                    if (rel) mbar_arrive_cluster(s_bar + 256 + 5 * 8, tid & 3);
                    fence_regs(acc);
                    if (tid == 0) TS(3, 3);
                } else {
                    wgmma_ss1_n128<0, 1>(z2, da[kk], db[kk]);
                }
                if (kk == 3) wg_commit();
                const float2 c2 = lds64f(s_cs + 512 + (j * 8 + q * 2) * 4);
                z1[2 * j] = pack_bf16(gelu_h(fmaf(p0.y, c2.x, acc[4 * j] * p0.x)), gelu_h(fmaf(p0.y, c2.y, acc[4 * j + 1] * p0.x)));
                z1[2 * j + 1] = pack_bf16(gelu_h(fmaf(p1.y, c2.x, acc[4 * j + 2] * p1.x)), gelu_h(fmaf(p1.y, c2.y, acc[4 * j + 3] * p1.x)));
                asm volatile("" : "+r"(z1[2 * j]), "+r"(z1[2 * j + 1]));
            }
            desc_add4(da, 1024);
            desc_add4(db, 1024);
        }
        if (tid == 0) TS(4, 0);
        wg_wait<1>();
        if (rel) mbar_arrive_cluster(s_bar + 256 + 2 * 8, tid & 3);
        {
            int s = 4, sp = 3, ph = 0;
#pragma unroll 1
            for (int i = 4; i < 32; i++) {
                mbar_wait(s_bar + 192 + s * 8, ph);
                if (tid == 0) TS(4, 8 + i);
                mma_kb(z2, da, db, 1);
                const uint32_t inc = s == 5 ? -5 * 1024 : 1024;
                desc_add4(da, inc);
                desc_add4(db, inc);
                wg_wait<1>();
                if (rel) mbar_arrive_cluster(s_bar + 256 + sp * 8, tid & 3);
                sp = s;
                if (++s == 6) { s = 0; ph ^= 1; }
            }
        }
        wg_wait<0>();
        fence_regs(z2);
        if (rel) mbar_arrive_cluster(s_bar + 256 + 1 * 8, tid & 3);
        if (tid == 0) TS(4, 3);
#pragma unroll
        for (int j = 0; j < 16; j++) {
            z1[2 * j] = pack_bf16(bf_lo(z1[2 * j]) * (z2[4 * j] + b0), bf_hi(z1[2 * j]) * (z2[4 * j + 1] + b0));
            z1[2 * j + 1] = pack_bf16(bf_lo(z1[2 * j + 1]) * (z2[4 * j + 2] + b1), bf_hi(z1[2 * j + 1]) * (z2[4 * j + 3] + b1));
        }
        const uint32_t stg = sb + 6 * 16384 + row * 128;
#pragma unroll
        for (int j = 0; j < 16; j += 2)
            stsm4(stg + (j >> 3) * 16384 + ((((j & 7) + (lane >> 4)) ^ (row & 7)) << 4), z1[2 * j], z1[2 * j + 1], z1[2 * j + 2], z1[2 * j + 3]);
        fence_proxy_async();
        __syncwarp();
        if (lane == 0) mbar_arrive(s_bar + 320 + wg * 8);
        float o[40];
        mbar_wait(s_bar + 192 + 2 * 8, 1);
        mbar_wait(s_bar + 192 + 3 * 8, 1);
#pragma unroll
        for (int j = 0; j < 10; j += 2) {
            uint32_t v[4];
            ldsm4(sb + (2 + (j >> 3)) * 16384 + row * 128 + ((((j & 7) + (lane >> 4)) ^ (row & 7)) << 4), v[0], v[1], v[2], v[3]);
#pragma unroll
            for (int e = 0; e < 4; e++) { o[4 * j + 2 * e] = bf_lo(v[e]); o[4 * j + 2 * e + 1] = bf_hi(v[e]); }
        }
        fence_regs(o);
#pragma unroll
        for (int kk = 0; kk < 4; kk++) {
            da[kk] = desc64(desc_lo(sb + 6 * 16384 + wg * 8192 + kk * 32, 16), SW_HI);
            db[kk] = desc64(desc_lo(s_b + 2 * 16384 + kk * 32, 16), SW_HI);
        }
        mbar_wait(s_bar + 320 + wg * 8, 1);
        {
            int s = 2, sp = 0, ph = 1;
#pragma unroll 1
            for (int j = 0; j < 14; j++) {
                mbar_wait(s_bar + 192 + s * 8, ph);
                if (tid == 0) TS(5, 8 + j);
                wg_fence();
#pragma unroll
                for (int kk = 0; kk < 4; kk++) wgmma_ss1_n80<0, 0>(o, da[kk], db[kk]);
                wg_commit();
                desc_add4(da, s == 5 ? -5 * 1024 : j == 1 ? -3 * 1024 : 1024);
                desc_add4(db, s == 5 ? -5 * 1024 : 1024);
                wg_wait<1>();
                if (rel && j >= 1 && j <= 8) mbar_arrive_cluster(s_bar + 256 + sp * 8, tid & 3);
                sp = s;
                if (++s == 6) { s = 0; ph ^= 1; }
            }
        }
        wg_wait<0>();
        fence_regs(o);
        if (tid == 0) TS(5, 3);
        const uint32_t ostg = s_b + (warp >> 1) * 16384 + 10240 + (warp & 1) * 2560;
#pragma unroll
        for (int j = 0; j < 10; j += 2)
            stsm4(ostg + (lane & 15) * 160 + (j + (lane >> 4)) * 16, pack_bf16(o[4 * j], o[4 * j + 1]), pack_bf16(o[4 * j + 2], o[4 * j + 3]),
                  pack_bf16(o[4 * j + 4], o[4 * j + 5]), pack_bf16(o[4 * j + 6], o[4 * j + 7]));
        fence_proxy_async();
        __syncwarp();
        if (lane == 0) {
            tma_store_2d(&tm.out, ostg, m.ftile * 80, m.tblk * 128 + warp * 16);
            bulk_commit();
            if (tid == 0) TS(5, 4);
            bulk_wait_read();
        }
        if (tid == 0) TS(5, 5);
    }
}

typedef CUresult (*EncodeFn)(CUtensorMap*, CUtensorMapDataType, cuuint32_t, void*, const cuuint64_t*, const cuuint64_t*, const cuuint32_t*,
                             const cuuint32_t*, CUtensorMapInterleave, CUtensorMapSwizzle, CUtensorMapL2promotion, CUtensorMapFloatOOBfill);

static CUtensorMap map2d(EncodeFn enc, const void* p, uint64_t cols, uint64_t rows, uint32_t bc, uint32_t br, CUtensorMapSwizzle sw = CU_TENSOR_MAP_SWIZZLE_128B) {
    CUtensorMap tm;
    cuuint64_t gd[2] = {cols, rows}, gs[1] = {cols * 2};
    cuuint32_t box[2] = {bc, br}, es[2] = {1, 1};
    enc(&tm, CU_TENSOR_MAP_DATA_TYPE_BFLOAT16, 2, (void*)p, gd, gs, box, es, CU_TENSOR_MAP_INTERLEAVE_NONE, sw,
        CU_TENSOR_MAP_L2_PROMOTION_L2_128B, CU_TENSOR_MAP_FLOAT_OOB_FILL_NONE);
    return tm;
}

template <typename... KArgs, typename... Args>
static void launch(void (*kern)(KArgs...), int grid, int block, int smem, bool pdl, Args... args) {
    cudaFuncSetAttribute(kern, cudaFuncAttributeMaxDynamicSharedMemorySize, smem);
    cudaLaunchConfig_t cfg = {};
    cfg.gridDim = dim3(grid); cfg.blockDim = dim3(block); cfg.dynamicSmemBytes = smem; cfg.stream = cudaStreamPerThread;
    cudaLaunchAttribute at[1];
    at[0].id = cudaLaunchAttributeProgrammaticStreamSerialization;
    at[0].val.programmaticStreamSerializationAllowed = 1;
    cfg.attrs = at; cfg.numAttrs = pdl ? 1 : 0;
    cudaLaunchKernelEx(&cfg, kern, args...);
}

extern "C" void kernel_launch(void* const* d_in, const int* in_sizes, int n_in, void* d_out, int out_size) {
    const bf16* x = (const bf16*)d_in[0];
    const bf16* wqkv = (const bf16*)d_in[1];
    const bf16* wo = (const bf16*)d_in[2];
    const bf16* w_in = (const bf16*)d_in[4];
    const bf16* w_sp = (const bf16*)d_in[5];
    const bf16* b_sp = (const bf16*)d_in[6];
    const bf16* w_out = (const bf16*)d_in[7];
    void* fn = nullptr;
    cudaDriverEntryPointQueryResult qr;
    cudaGetDriverEntryPoint("cuTensorMapEncodeTiled", &fn, cudaEnableDefault, &qr);
    EncodeFn enc = (EncodeFn)fn;
    void *p_o, *p_h, *p_z2, *p_u;
    cudaGetSymbolAddress(&p_o, g_o); cudaGetSymbolAddress(&p_h, g_h); cudaGetSymbolAddress(&p_z2, g_z2);
    cudaGetSymbolAddress(&p_u, g_u);

    CUtensorMap tm_x = map2d(enc, x, 512, 2048, 64, 128);
    CUtensorMap tm_wqkv;
    {
        cuuint64_t gd[3] = {64, 512, 24}, gs[2] = {1536 * 2, 128};
        cuuint32_t box[3] = {64, 32, 3}, es[3] = {1, 1, 1};
        enc(&tm_wqkv, CU_TENSOR_MAP_DATA_TYPE_BFLOAT16, 3, (void*)wqkv, gd, gs, box, es, CU_TENSOR_MAP_INTERLEAVE_NONE, CU_TENSOR_MAP_SWIZZLE_128B,
            CU_TENSOR_MAP_L2_PROMOTION_L2_128B, CU_TENSOR_MAP_FLOAT_OOB_FILL_NONE);
    }
    CUtensorMap tm_o = map2d(enc, p_o, 512, 2048, 64, 64);
    CUtensorMap tm_wo = map2d(enc, wo, 512, 512, 64, 128);
    CUtensorMap tm_hs = map2d(enc, p_h, 512, 2048, 64, 16);
    Maps4 m4;
    for (int i = 0; i < 2; i++) {
        m4.h[i] = map2d(enc, p_h, 512, 2048, 64, 64 << i);
        m4.win[i] = map2d(enc, w_in, 1792, 512, 64, 64 >> i);
        m4.wsp[i] = map2d(enc, w_sp, 2048, 2048, 64, 64 << i);
        m4.z2[i] = map2d(enc, p_z2, 896, 2048, 64, 64 >> i);
        m4.u[i] = map2d(enc, p_u, 896, 2048, 64, 64 << i);
    }
    m4.out = map2d(enc, d_out, 512, 2048, 80, 16, CU_TENSOR_MAP_SWIZZLE_NONE);

    launch(k_qkv, 128, 416, G1_SMEM, false, tm_x, tm_wqkv, x, wqkv);
    launch(k_attn, 132, 512, AT_SMEM, true, w_in, w_sp, w_out, wo);
    launch(k_proj<8, 8, true>, 128, 288, 8 * 16384 + 8 * 8192 + 16384 + 256 + 1024, true, tm_o, tm_wo, tm_x, tm_hs);
    launch(k_zg, 112, 320, G4_SMEM, true, m4, b_sp);
}
```
